```python
import torch

def _softmax(x, axis=-1):
    return torch.softmax(x, dim=axis)
def _gelu(x):
    return torch.nn.functional.gelu(x, approximate="tanh")
def _silu(x):
    return torch.nn.functional.silu(x)
def _sigmoid(x):
    return torch.sigmoid(x)
def _layernorm(x, axis=-1, eps=1e-5):
    m = x.mean(dim=axis, keepdim=True)
    v = x.var(dim=axis, keepdim=True, unbiased=False)
    return (x - m) / torch.sqrt(v + eps)
def _scatter_add(tgt, idx, src, axis=0):
    return tgt.clone().index_add_(axis, idx, src)
def _segment_sum(src, seg, n):
    out = torch.zeros((n,) + src.shape[1:], dtype=src.dtype)
    return out.index_add_(0, seg, src)
def _pad(x, pw):
    flat = tuple(v for pair in reversed(pw) for v in pair)
    return torch.nn.functional.pad(x, flat)

kernel_name = 'concat_heads__linear_kernel_hedgehog__ssm_conv_s4d__prompt'

def setup_inputs():

    _w = (lambda a: (lambda t: t.to(torch.bfloat16) if t.is_floating_point() else t)(torch.as_tensor(a)))
    def _A_setup():
        B, S, D, H = 1, 2048, 512, 32
        Dh = D // H
        return {
            "x": _w((lambda *s: torch.randn(*s, dtype=torch.bfloat16) * 0.4)(B, S, D)),
            "wqkv": _w((lambda *s: torch.randn(*s, dtype=torch.bfloat16) * 0.4)(D, 3 * D)),
            "w_phi": _w((lambda *s: torch.randn(*s, dtype=torch.bfloat16) * 0.4)(H, Dh, Dh) * (Dh ** -0.5)),
            "wo": _w((lambda *s: torch.randn(*s, dtype=torch.bfloat16) * 0.05)(D, D)),
        }
    _A_in = _A_setup()

    def _B_setup():
        Bsz, L, D, N = 1, 2048, 512, 128
        return {
            "u": _w((lambda *s: torch.randn(*s, dtype=torch.bfloat16) * 0.05)(Bsz, L, D)),
            "log_A_real": _w((lambda *s: torch.randn(*s, dtype=torch.bfloat16) * 3.2)(D, N) * 0.5),
            "A_imag": _w((lambda *s: torch.randn(*s, dtype=torch.bfloat16) * 0.2)(D, N) * 3.14),
            "C_real": _w((lambda *s: torch.randn(*s, dtype=torch.bfloat16) * 3.2)(D, N) / N ** 0.5),
            "C_imag": _w((lambda *s: torch.randn(*s, dtype=torch.bfloat16) * 3.2)(D, N) / N ** 0.5),
            "log_dt": _w((lambda *s: torch.randn(*s, dtype=torch.bfloat16) * 0.2)(D) * 0.5 - 4.0),
            "D_skip": _w((lambda *s: torch.randn(*s, dtype=torch.bfloat16) * 0.4)(D)),
        }
    _B_in = _B_setup()

    return {
        "A_x": _A_in["x"],
        "A_wqkv": _A_in["wqkv"],
        "A_w_phi": _A_in["w_phi"],
        "A_wo": _A_in["wo"],
        "B_u": _B_in["u"],
        "B_log_A_real": _B_in["log_A_real"],
        "B_A_imag": _B_in["A_imag"],
        "B_C_real": _B_in["C_real"],
        "B_C_imag": _B_in["C_imag"],
        "B_log_dt": _B_in["log_dt"],
        "B_D_skip": _B_in["D_skip"],
    }

def reference(A_x, A_wqkv, A_w_phi, A_wo, B_u, B_log_A_real, B_A_imag, B_C_real, B_C_imag, B_log_dt, B_D_skip):
    def _A_ref(x, wqkv, w_phi, wo):
        B, S, D = x.shape
        H = 32; Dh = D // H
        qkv = (lambda x, *d: x.permute(*d))((x @ wqkv).reshape(B, S, 3, H, Dh), 2, 0, 3, 1, 4)
        q, k, v = qkv[0], qkv[1], qkv[2]
        pq = torch.einsum("bhsd,hdf->bhsf", q, w_phi)
        pk = torch.einsum("bhsd,hdf->bhsf", k, w_phi)
        phi_q = torch.concatenate([_softmax(pq, axis=-1), _softmax(-pq, axis=-1)], axis=-1)
        phi_k = torch.concatenate([_softmax(pk, axis=-1), _softmax(-pk, axis=-1)], axis=-1)
        kv = torch.einsum("bhsf,bhsd->bhfd", phi_k, v)
        z  = torch.einsum("bhsf->bhf", phi_k)
        num = torch.einsum("bhqf,bhfd->bhqd", phi_q, kv)
        den = torch.einsum("bhqf,bhf->bhq", phi_q, z)[..., None] + 1e-6
        o = num / den
        return (lambda x, *d: x.permute(*d))(o, 0, 2, 1, 3).reshape(B, S, D) @ wo

    def _B_ref(u, log_A_real, A_imag, C_real, C_imag, log_dt, D_skip):
        L = u.shape[1]
        dt = torch.exp(log_dt)
        A = -torch.exp(log_A_real) + 1j * A_imag
        C = (C_real + 1j * C_imag) * dt[:, None]
        pos = (lambda x, dt: x.to(dt))(torch.arange(L), log_dt.dtype)
        P = torch.exp((A * dt[:, None])[:, :, None] * pos[None, None, :])
        K = 2.0 * torch.einsum("dn,dnl->dl", C, P).real
        L2 = 2 * L
        u_t = (lambda x, *d: x.permute(*d))(u, 0, 2, 1)
        Kf = (lambda x, *a, **k: torch.fft.rfft(x.float(), *a, **k))(K, L2)
        Uf = (lambda x, *a, **k: torch.fft.rfft(x.float(), *a, **k))(u_t, L2)
        y = (lambda x, *a, **k: torch.fft.irfft(x, *a, **k).to(torch.bfloat16))(Uf * Kf[None, :, :], L2)[:, :, :L]
        y = (lambda x, *d: x.permute(*d))(y, 0, 2, 1)
        return y + u * D_skip[None, None, :]

    a = _A_ref(A_x, A_wqkv, A_w_phi, A_wo)
    b = _B_ref(B_u, B_log_A_real, B_A_imag, B_C_real, B_C_imag, B_log_dt, B_D_skip)
    return torch.concatenate([a, b], axis=-1)
```

```cpp
#include <cuda_runtime.h>
#include <cuda_bf16.h>
#include <cuda.h>
#include <stdint.h>

#define TL(slot, cond)
#define TL_DUMP(lo, hi, cond)

__device__ uint4 g_kvp[8 * 16 * 16 * 32];
__device__ uint4 g_kvf[8 * 512];
__device__ uint4 g_o[128 * 32 * 32];
__device__ uint4 g_ut[512 * 256];
__device__ uint4 g_y[512 * 8 * 32];
__device__ unsigned g_flag[32 * 32];
__device__ unsigned g_epoch[128 + 512];

__device__ __forceinline__ uint32_t smem_u32(const void* p) { return (uint32_t)__cvta_generic_to_shared(p); }
__device__ __forceinline__ void mbar_init(uint32_t bar, uint32_t cnt) { asm volatile("mbarrier.init.shared::cta.b64 [%0], %1;" :: "r"(bar), "r"(cnt)); }
__device__ __forceinline__ void mbar_expect_tx(uint32_t bar, uint32_t bytes) { asm volatile("mbarrier.arrive.expect_tx.shared::cta.b64 _, [%0], %1;" :: "r"(bar), "r"(bytes) : "memory"); }
__device__ __forceinline__ void mbar_arrive(uint32_t bar) { asm volatile("mbarrier.arrive.shared::cta.b64 _, [%0];" :: "r"(bar) : "memory"); }
__device__ __forceinline__ void mbar_wait(uint32_t bar, uint32_t parity) {
  asm volatile("{\n.reg .pred p, q;\n.reg .u32 n;\nmov.u32 n, 0;\n"
               "W_%=:\nmbarrier.try_wait.parity.shared::cta.b64 p, [%0], %1;\nadd.u32 n, n, 1;\nsetp.lt.and.u32 q, n, 262144, !p;\n@q bra W_%=;\n}" :: "r"(bar), "r"(parity) : "memory");
}
__device__ __forceinline__ bool mbar_test(uint32_t bar, uint32_t parity) {
  uint32_t d; asm volatile("{\n.reg .pred p;\nmbarrier.test_wait.parity.shared::cta.b64 p, [%1], %2;\nselp.u32 %0, 1, 0, p;\n}" : "=r"(d) : "r"(bar), "r"(parity) : "memory"); return d;
}
__device__ __forceinline__ bool mbar_try(uint32_t bar, uint32_t parity) {
  uint32_t d; asm volatile("{\n.reg .pred p;\nmbarrier.try_wait.parity.shared::cta.b64 p, [%1], %2, 64;\nselp.u32 %0, 1, 0, p;\n}" : "=r"(d) : "r"(bar), "r"(parity) : "memory"); return d;
}
#define bar_sync(id, n) asm volatile("bar.sync " #id ", " #n ";" ::: "memory")
__device__ __forceinline__ void fence_async() { asm volatile("fence.proxy.async.shared::cta;" ::: "memory"); }
__device__ __forceinline__ void tma2d(uint32_t dst, const CUtensorMap* m, int c0, int c1, uint32_t bar) {
  asm volatile("cp.async.bulk.tensor.2d.shared::cluster.global.mbarrier::complete_tx::bytes [%0], [%1, {%3, %4}], [%2];" :: "r"(dst), "l"(m), "r"(bar), "r"(c0), "r"(c1) : "memory");
}
__device__ __forceinline__ void tma3d(uint32_t dst, const CUtensorMap* m, int c0, int c1, int c2, uint32_t bar) {
  asm volatile("cp.async.bulk.tensor.3d.shared::cluster.global.mbarrier::complete_tx::bytes [%0], [%1, {%3, %4, %5}], [%2];" :: "r"(dst), "l"(m), "r"(bar), "r"(c0), "r"(c1), "r"(c2) : "memory");
}
__device__ __forceinline__ uint64_t make_desc(uint32_t addr, uint32_t lbo, uint32_t sbo, int swz) {
  const uint32_t lo = (addr >> 4) + ((lbo >> 4) << 16), hi = (sbo >> 4) | ((uint32_t)swz << 30);
  uint64_t d; asm("mov.b64 %0, {%1,%2};" : "=l"(d) : "r"(lo), "r"(hi)); return d;
}
__device__ __forceinline__ void wg_fence() { asm volatile("wgmma.fence.sync.aligned;" ::: "memory"); }
__device__ __forceinline__ void wg_commit() { asm volatile("wgmma.commit_group.sync.aligned;" ::: "memory"); }
template <int N> __device__ __forceinline__ void wg_wait() { asm volatile("wgmma.wait_group.sync.aligned %0;" :: "n"(N) : "memory"); }
template <int N> __device__ __forceinline__ void pin(float* d) {
#pragma unroll
  for (int i = 0; i < N; i++) asm volatile("" : "+f"(d[i]) :: "memory");
}
__device__ __forceinline__ void wg_ss192(float* d, uint64_t da, uint64_t db, int sd) {
  asm volatile("{\n.reg .pred p;\nsetp.ne.b32 p, %98, 0;\nwgmma.mma_async.sync.aligned.m64n192k16.f32.bf16.bf16 {%0,%1,%2,%3,%4,%5,%6,%7,%8,%9,%10,%11,%12,%13,%14,%15,%16,%17,%18,%19,%20,%21,%22,%23,%24,%25,%26,%27,%28,%29,%30,%31,%32,%33,%34,%35,%36,%37,%38,%39,%40,%41,%42,%43,%44,%45,%46,%47,%48,%49,%50,%51,%52,%53,%54,%55,%56,%57,%58,%59,%60,%61,%62,%63,%64,%65,%66,%67,%68,%69,%70,%71,%72,%73,%74,%75,%76,%77,%78,%79,%80,%81,%82,%83,%84,%85,%86,%87,%88,%89,%90,%91,%92,%93,%94,%95}, %96, %97, p, 1, 1, 0, 1;\n}"
    : "+f"(d[0]),"+f"(d[1]),"+f"(d[2]),"+f"(d[3]),"+f"(d[4]),"+f"(d[5]),"+f"(d[6]),"+f"(d[7]),"+f"(d[8]),"+f"(d[9]),"+f"(d[10]),"+f"(d[11]),"+f"(d[12]),"+f"(d[13]),"+f"(d[14]),"+f"(d[15]),"+f"(d[16]),"+f"(d[17]),"+f"(d[18]),"+f"(d[19]),"+f"(d[20]),"+f"(d[21]),"+f"(d[22]),"+f"(d[23]),"+f"(d[24]),"+f"(d[25]),"+f"(d[26]),"+f"(d[27]),"+f"(d[28]),"+f"(d[29]),"+f"(d[30]),"+f"(d[31]),"+f"(d[32]),"+f"(d[33]),"+f"(d[34]),"+f"(d[35]),"+f"(d[36]),"+f"(d[37]),"+f"(d[38]),"+f"(d[39]),"+f"(d[40]),"+f"(d[41]),"+f"(d[42]),"+f"(d[43]),"+f"(d[44]),"+f"(d[45]),"+f"(d[46]),"+f"(d[47]),"+f"(d[48]),"+f"(d[49]),"+f"(d[50]),"+f"(d[51]),"+f"(d[52]),"+f"(d[53]),"+f"(d[54]),"+f"(d[55]),"+f"(d[56]),"+f"(d[57]),"+f"(d[58]),"+f"(d[59]),"+f"(d[60]),"+f"(d[61]),"+f"(d[62]),"+f"(d[63]),"+f"(d[64]),"+f"(d[65]),"+f"(d[66]),"+f"(d[67]),"+f"(d[68]),"+f"(d[69]),"+f"(d[70]),"+f"(d[71]),"+f"(d[72]),"+f"(d[73]),"+f"(d[74]),"+f"(d[75]),"+f"(d[76]),"+f"(d[77]),"+f"(d[78]),"+f"(d[79]),"+f"(d[80]),"+f"(d[81]),"+f"(d[82]),"+f"(d[83]),"+f"(d[84]),"+f"(d[85]),"+f"(d[86]),"+f"(d[87]),"+f"(d[88]),"+f"(d[89]),"+f"(d[90]),"+f"(d[91]),"+f"(d[92]),"+f"(d[93]),"+f"(d[94]),"+f"(d[95]) : "l"(da), "l"(db), "r"(sd));
}
__device__ __forceinline__ void wg_ss128(float* d, uint64_t da, uint64_t db, int sd) {
  asm volatile("{\n.reg .pred p;\nsetp.ne.b32 p, %66, 0;\nwgmma.mma_async.sync.aligned.m64n128k16.f32.bf16.bf16 {%0,%1,%2,%3,%4,%5,%6,%7,%8,%9,%10,%11,%12,%13,%14,%15,%16,%17,%18,%19,%20,%21,%22,%23,%24,%25,%26,%27,%28,%29,%30,%31,%32,%33,%34,%35,%36,%37,%38,%39,%40,%41,%42,%43,%44,%45,%46,%47,%48,%49,%50,%51,%52,%53,%54,%55,%56,%57,%58,%59,%60,%61,%62,%63}, %64, %65, p, 1, 1, 0, 1;\n}"
    : "+f"(d[0]),"+f"(d[1]),"+f"(d[2]),"+f"(d[3]),"+f"(d[4]),"+f"(d[5]),"+f"(d[6]),"+f"(d[7]),"+f"(d[8]),"+f"(d[9]),"+f"(d[10]),"+f"(d[11]),"+f"(d[12]),"+f"(d[13]),"+f"(d[14]),"+f"(d[15]),"+f"(d[16]),"+f"(d[17]),"+f"(d[18]),"+f"(d[19]),"+f"(d[20]),"+f"(d[21]),"+f"(d[22]),"+f"(d[23]),"+f"(d[24]),"+f"(d[25]),"+f"(d[26]),"+f"(d[27]),"+f"(d[28]),"+f"(d[29]),"+f"(d[30]),"+f"(d[31]),"+f"(d[32]),"+f"(d[33]),"+f"(d[34]),"+f"(d[35]),"+f"(d[36]),"+f"(d[37]),"+f"(d[38]),"+f"(d[39]),"+f"(d[40]),"+f"(d[41]),"+f"(d[42]),"+f"(d[43]),"+f"(d[44]),"+f"(d[45]),"+f"(d[46]),"+f"(d[47]),"+f"(d[48]),"+f"(d[49]),"+f"(d[50]),"+f"(d[51]),"+f"(d[52]),"+f"(d[53]),"+f"(d[54]),"+f"(d[55]),"+f"(d[56]),"+f"(d[57]),"+f"(d[58]),"+f"(d[59]),"+f"(d[60]),"+f"(d[61]),"+f"(d[62]),"+f"(d[63]) : "l"(da), "l"(db), "r"(sd));
}
__device__ __forceinline__ void wg_ss64(float* d, uint64_t da, uint64_t db, int sd) {
  asm volatile("{\n.reg .pred p;\nsetp.ne.b32 p, %34, 0;\nwgmma.mma_async.sync.aligned.m64n64k16.f32.bf16.bf16 {%0,%1,%2,%3,%4,%5,%6,%7,%8,%9,%10,%11,%12,%13,%14,%15,%16,%17,%18,%19,%20,%21,%22,%23,%24,%25,%26,%27,%28,%29,%30,%31}, %32, %33, p, 1, 1, 0, 1;\n}"
    : "+f"(d[0]),"+f"(d[1]),"+f"(d[2]),"+f"(d[3]),"+f"(d[4]),"+f"(d[5]),"+f"(d[6]),"+f"(d[7]),"+f"(d[8]),"+f"(d[9]),"+f"(d[10]),"+f"(d[11]),"+f"(d[12]),"+f"(d[13]),"+f"(d[14]),"+f"(d[15]),"+f"(d[16]),"+f"(d[17]),"+f"(d[18]),"+f"(d[19]),"+f"(d[20]),"+f"(d[21]),"+f"(d[22]),"+f"(d[23]),"+f"(d[24]),"+f"(d[25]),"+f"(d[26]),"+f"(d[27]),"+f"(d[28]),"+f"(d[29]),"+f"(d[30]),"+f"(d[31]) : "l"(da), "l"(db), "r"(sd));
}
__device__ __forceinline__ void wg_ss24(float* d, uint64_t da, uint64_t db, int sd) {
  asm volatile("{\n.reg .pred p;\nsetp.ne.b32 p, %14, 0;\nwgmma.mma_async.sync.aligned.m64n24k16.f32.bf16.bf16 {%0,%1,%2,%3,%4,%5,%6,%7,%8,%9,%10,%11}, %12, %13, p, 1, 1, 0, 1;\n}"
    : "+f"(d[0]),"+f"(d[1]),"+f"(d[2]),"+f"(d[3]),"+f"(d[4]),"+f"(d[5]),"+f"(d[6]),"+f"(d[7]),"+f"(d[8]),"+f"(d[9]),"+f"(d[10]),"+f"(d[11]) : "l"(da), "l"(db), "r"(sd));
}
__device__ __forceinline__ void wg_tt32(float* d, uint64_t da, uint64_t db, int sd) {
  asm volatile("{\n.reg .pred p;\nsetp.ne.b32 p, %18, 0;\nwgmma.mma_async.sync.aligned.m64n32k16.f32.bf16.bf16 {%0,%1,%2,%3,%4,%5,%6,%7,%8,%9,%10,%11,%12,%13,%14,%15}, %16, %17, p, 1, 1, 1, 1;\n}"
    : "+f"(d[0]),"+f"(d[1]),"+f"(d[2]),"+f"(d[3]),"+f"(d[4]),"+f"(d[5]),"+f"(d[6]),"+f"(d[7]),"+f"(d[8]),"+f"(d[9]),"+f"(d[10]),"+f"(d[11]),"+f"(d[12]),"+f"(d[13]),"+f"(d[14]),"+f"(d[15]) : "l"(da), "l"(db), "r"(sd));
}
__device__ __forceinline__ void wg_tt40(float* d, uint64_t da, uint64_t db, int sd) {
  asm volatile("{\n.reg .pred p;\nsetp.ne.b32 p, %22, 0;\nwgmma.mma_async.sync.aligned.m64n40k16.f32.bf16.bf16 {%0,%1,%2,%3,%4,%5,%6,%7,%8,%9,%10,%11,%12,%13,%14,%15,%16,%17,%18,%19}, %20, %21, p, 1, 1, 1, 1;\n}"
    : "+f"(d[0]),"+f"(d[1]),"+f"(d[2]),"+f"(d[3]),"+f"(d[4]),"+f"(d[5]),"+f"(d[6]),"+f"(d[7]),"+f"(d[8]),"+f"(d[9]),"+f"(d[10]),"+f"(d[11]),"+f"(d[12]),"+f"(d[13]),"+f"(d[14]),"+f"(d[15]),"+f"(d[16]),"+f"(d[17]),"+f"(d[18]),"+f"(d[19]) : "l"(da), "l"(db), "r"(sd));
}
__device__ __forceinline__ void wg_tt8(float* d, uint64_t da, uint64_t db, int sd) {
  asm volatile("{\n.reg .pred p;\nsetp.ne.b32 p, %6, 0;\nwgmma.mma_async.sync.aligned.m64n8k16.f32.bf16.bf16 {%0,%1,%2,%3}, %4, %5, p, 1, 1, 1, 1;\n}"
    : "+f"(d[0]),"+f"(d[1]),"+f"(d[2]),"+f"(d[3]) : "l"(da), "l"(db), "r"(sd));
}
__device__ __forceinline__ void wg_rs16(float* d, uint32_t a0, uint32_t a1, uint32_t a2, uint32_t a3, uint64_t db, int sd) {
  asm volatile("{\n.reg .pred p;\nsetp.ne.b32 p, %13, 0;\nwgmma.mma_async.sync.aligned.m64n16k16.f32.bf16.bf16 {%0,%1,%2,%3,%4,%5,%6,%7}, {%8,%9,%10,%11}, %12, p, 1, 1, 1;\n}"
    : "+f"(d[0]),"+f"(d[1]),"+f"(d[2]),"+f"(d[3]),"+f"(d[4]),"+f"(d[5]),"+f"(d[6]),"+f"(d[7]) : "r"(a0), "r"(a1), "r"(a2), "r"(a3), "l"(db), "r"(sd));
}
__device__ __forceinline__ void wg_rs24(float* d, uint32_t a0, uint32_t a1, uint32_t a2, uint32_t a3, uint64_t db, int sd) {
  asm volatile("{\n.reg .pred p;\nsetp.ne.b32 p, %17, 0;\nwgmma.mma_async.sync.aligned.m64n24k16.f32.bf16.bf16 {%0,%1,%2,%3,%4,%5,%6,%7,%8,%9,%10,%11}, {%12,%13,%14,%15}, %16, p, 1, 1, 1;\n}"
    : "+f"(d[0]),"+f"(d[1]),"+f"(d[2]),"+f"(d[3]),"+f"(d[4]),"+f"(d[5]),"+f"(d[6]),"+f"(d[7]),"+f"(d[8]),"+f"(d[9]),"+f"(d[10]),"+f"(d[11]) : "r"(a0), "r"(a1), "r"(a2), "r"(a3), "l"(db), "r"(sd));
}
__device__ __forceinline__ void wg_rs128(float* d, uint32_t a0, uint32_t a1, uint32_t a2, uint32_t a3, uint64_t db, int sd) {
  asm volatile("{\n.reg .pred p;\nsetp.ne.b32 p, %69, 0;\nwgmma.mma_async.sync.aligned.m64n128k16.f32.bf16.bf16 {%0,%1,%2,%3,%4,%5,%6,%7,%8,%9,%10,%11,%12,%13,%14,%15,%16,%17,%18,%19,%20,%21,%22,%23,%24,%25,%26,%27,%28,%29,%30,%31,%32,%33,%34,%35,%36,%37,%38,%39,%40,%41,%42,%43,%44,%45,%46,%47,%48,%49,%50,%51,%52,%53,%54,%55,%56,%57,%58,%59,%60,%61,%62,%63}, {%64,%65,%66,%67}, %68, p, 1, 1, 1;\n}"
    : "+f"(d[0]),"+f"(d[1]),"+f"(d[2]),"+f"(d[3]),"+f"(d[4]),"+f"(d[5]),"+f"(d[6]),"+f"(d[7]),"+f"(d[8]),"+f"(d[9]),"+f"(d[10]),"+f"(d[11]),"+f"(d[12]),"+f"(d[13]),"+f"(d[14]),"+f"(d[15]),"+f"(d[16]),"+f"(d[17]),"+f"(d[18]),"+f"(d[19]),"+f"(d[20]),"+f"(d[21]),"+f"(d[22]),"+f"(d[23]),"+f"(d[24]),"+f"(d[25]),"+f"(d[26]),"+f"(d[27]),"+f"(d[28]),"+f"(d[29]),"+f"(d[30]),"+f"(d[31]),"+f"(d[32]),"+f"(d[33]),"+f"(d[34]),"+f"(d[35]),"+f"(d[36]),"+f"(d[37]),"+f"(d[38]),"+f"(d[39]),"+f"(d[40]),"+f"(d[41]),"+f"(d[42]),"+f"(d[43]),"+f"(d[44]),"+f"(d[45]),"+f"(d[46]),"+f"(d[47]),"+f"(d[48]),"+f"(d[49]),"+f"(d[50]),"+f"(d[51]),"+f"(d[52]),"+f"(d[53]),"+f"(d[54]),"+f"(d[55]),"+f"(d[56]),"+f"(d[57]),"+f"(d[58]),"+f"(d[59]),"+f"(d[60]),"+f"(d[61]),"+f"(d[62]),"+f"(d[63]) : "r"(a0), "r"(a1), "r"(a2), "r"(a3), "l"(db), "r"(sd));
}
__device__ __forceinline__ void wg_rs64(float* d, uint32_t a0, uint32_t a1, uint32_t a2, uint32_t a3, uint64_t db, int sd) {
  asm volatile("{\n.reg .pred p;\nsetp.ne.b32 p, %37, 0;\nwgmma.mma_async.sync.aligned.m64n64k16.f32.bf16.bf16 {%0,%1,%2,%3,%4,%5,%6,%7,%8,%9,%10,%11,%12,%13,%14,%15,%16,%17,%18,%19,%20,%21,%22,%23,%24,%25,%26,%27,%28,%29,%30,%31}, {%32,%33,%34,%35}, %36, p, 1, 1, 1;\n}"
    : "+f"(d[0]),"+f"(d[1]),"+f"(d[2]),"+f"(d[3]),"+f"(d[4]),"+f"(d[5]),"+f"(d[6]),"+f"(d[7]),"+f"(d[8]),"+f"(d[9]),"+f"(d[10]),"+f"(d[11]),"+f"(d[12]),"+f"(d[13]),"+f"(d[14]),"+f"(d[15]),"+f"(d[16]),"+f"(d[17]),"+f"(d[18]),"+f"(d[19]),"+f"(d[20]),"+f"(d[21]),"+f"(d[22]),"+f"(d[23]),"+f"(d[24]),"+f"(d[25]),"+f"(d[26]),"+f"(d[27]),"+f"(d[28]),"+f"(d[29]),"+f"(d[30]),"+f"(d[31]) : "r"(a0), "r"(a1), "r"(a2), "r"(a3), "l"(db), "r"(sd));
}

__device__ __forceinline__ void mma16816(float* c, uint32_t a0, uint32_t a1, uint32_t a2, uint32_t a3, uint32_t b0, uint32_t b1) {
  asm volatile("mma.sync.aligned.m16n8k16.row.col.f32.bf16.bf16.f32 {%0,%1,%2,%3}, {%4,%5,%6,%7}, {%8,%9}, {%0,%1,%2,%3};"
    : "+f"(c[0]), "+f"(c[1]), "+f"(c[2]), "+f"(c[3]) : "r"(a0), "r"(a1), "r"(a2), "r"(a3), "r"(b0), "r"(b1));
}
__device__ __forceinline__ uint32_t pack_bf16(float lo, float hi) { uint32_t r; asm("cvt.rn.bf16x2.f32 %0, %1, %2;" : "=r"(r) : "f"(hi), "f"(lo)); return r; }
__device__ __forceinline__ float bf_lo(uint32_t v) { return __uint_as_float(v << 16); }
__device__ __forceinline__ float bf_hi(uint32_t v) { return __uint_as_float(v & 0xFFFF0000u); }
__device__ __forceinline__ uint32_t bmax2(uint32_t a, uint32_t b) { uint32_t r; asm("max.bf16x2 %0, %1, %2;" : "=r"(r) : "r"(a), "r"(b)); return r; }
__device__ __forceinline__ uint32_t bmin2(uint32_t a, uint32_t b) { uint32_t r; asm("min.bf16x2 %0, %1, %2;" : "=r"(r) : "r"(a), "r"(b)); return r; }
__device__ __forceinline__ float ex2(float x) { float r; asm("ex2.approx.ftz.f32 %0, %1;" : "=f"(r) : "f"(x)); return r; }
__device__ __forceinline__ float rcp(float x) { float r; asm("rcp.approx.ftz.f32 %0, %1;" : "=f"(r) : "f"(x)); return r; }
__device__ __forceinline__ void stsm4(uint32_t addr, uint32_t r0, uint32_t r1, uint32_t r2, uint32_t r3) {
  asm volatile("stmatrix.sync.aligned.m8n8.x4.shared.b16 [%0], {%1,%2,%3,%4};" :: "r"(addr), "r"(r0), "r"(r1), "r"(r2), "r"(r3) : "memory");
}
__device__ __forceinline__ void ldsm4(uint32_t addr, uint32_t& r0, uint32_t& r1, uint32_t& r2, uint32_t& r3) {
  asm volatile("ldmatrix.sync.aligned.m8n8.x4.shared.b16 {%0,%1,%2,%3}, [%4];" : "=r"(r0), "=r"(r1), "=r"(r2), "=r"(r3) : "r"(addr) : "memory");
}
__device__ __forceinline__ void sts32(uint32_t a, uint32_t v) { asm volatile("st.shared.b32 [%0], %1;" :: "r"(a), "r"(v) : "memory"); }
__device__ __forceinline__ void sts16(uint32_t a, uint32_t v) { asm volatile("st.shared.b16 [%0], %1;" :: "r"(a), "h"((uint16_t)v) : "memory"); }
__device__ __forceinline__ void sts64(uint32_t a, uint32_t x, uint32_t y) { asm volatile("st.shared.v2.b32 [%0], {%1,%2};" :: "r"(a), "r"(x), "r"(y) : "memory"); }
__device__ __forceinline__ void sts128(uint32_t a, uint32_t x, uint32_t y, uint32_t z, uint32_t w) { asm volatile("st.shared.v4.b32 [%0], {%1,%2,%3,%4};" :: "r"(a), "r"(x), "r"(y), "r"(z), "r"(w) : "memory"); }
__device__ __forceinline__ uint32_t lds16(uint32_t a) { uint16_t v; asm volatile("ld.shared.b16 %0, [%1];" : "=h"(v) : "r"(a) : "memory"); return v; }
__device__ __forceinline__ uint32_t lds32(uint32_t a) { uint32_t v; asm volatile("ld.shared.b32 %0, [%1];" : "=r"(v) : "r"(a) : "memory"); return v; }
__device__ __forceinline__ void lds64(uint32_t a, uint32_t& x, uint32_t& y) { asm volatile("ld.shared.v2.b32 {%0,%1}, [%2];" : "=r"(x), "=r"(y) : "r"(a) : "memory"); }
__device__ __forceinline__ void lds128(uint32_t a, uint32_t& x, uint32_t& y, uint32_t& z, uint32_t& w) { asm volatile("ld.shared.v4.b32 {%0,%1,%2,%3}, [%4];" : "=r"(x), "=r"(y), "=r"(z), "=r"(w) : "r"(a) : "memory"); }
__device__ __forceinline__ uint4 ld_pkt(const uint4* p) {
  uint4 v;
  asm volatile("{\n.reg .b128 t;\n.reg .b64 a, b;\nld.relaxed.gpu.global.b128 t, [%4];\nmov.b128 {a,b}, t;\nmov.b64 {%0,%1}, a;\nmov.b64 {%2,%3}, b;\n}"
               : "=r"(v.x), "=r"(v.y), "=r"(v.z), "=r"(v.w) : "l"(p) : "memory");
  return v;
}
__device__ __forceinline__ void ld_pkt_if(uint32_t c, uint4& v, const uint4* p) {
  asm volatile("{\n.reg .b128 t;\n.reg .b64 a, b;\n.reg .pred q;\nsetp.ne.u32 q, %5, 0;\nmov.b64 a, {%0,%1};\nmov.b64 b, {%2,%3};\nmov.b128 t, {a,b};\n"
               "@q ld.relaxed.gpu.global.b128 t, [%4];\nmov.b128 {a,b}, t;\nmov.b64 {%0,%1}, a;\nmov.b64 {%2,%3}, b;\n}"
               : "+r"(v.x), "+r"(v.y), "+r"(v.z), "+r"(v.w) : "l"(p), "r"(c) : "memory");
}
__device__ __forceinline__ void st_pkt(uint4* p, uint32_t x, uint32_t y, uint32_t z, uint32_t w) {
  asm volatile("{\n.reg .b128 t;\n.reg .b64 a, b;\nmov.b64 a, {%0,%1};\nmov.b64 b, {%2,%3};\nmov.b128 t, {a,b};\nst.relaxed.gpu.global.b128 [%4], t;\n}"
               :: "r"(x), "r"(y), "r"(z), "r"(w), "l"(p) : "memory");
}
__device__ __forceinline__ uint2 ldg64(const void* p) { uint2 v; asm volatile("ld.global.nc.v2.b32 {%0,%1}, [%2];" : "=r"(v.x), "=r"(v.y) : "l"(p)); return v; }

__device__ __forceinline__ uint4 ldg128(const void* p) { uint4 v; asm volatile("ld.global.nc.L2::128B.v4.b32 {%0,%1,%2,%3}, [%4];" : "=r"(v.x), "=r"(v.y), "=r"(v.z), "=r"(v.w) : "l"(p)); return v; }
__device__ __forceinline__ uint32_t mism(uint32_t a, uint32_t b, uint32_t t) { uint32_t r; asm("lop3.b32 %0, %1, %2, %3, 0x7E;" : "=r"(r) : "r"(a), "r"(b), "r"(t)); return r; }
__device__ __forceinline__ void prefetch_l2(const void* p, uint32_t bytes) { asm volatile("cp.async.bulk.prefetch.L2.global [%0], %1;" :: "l"(p), "r"(bytes)); }

constexpr int STAGE = 40960;
constexpr int SM_PK = 0;
constexpr int SM_V = 32768;
constexpr int ST_SZ = 53 * 128;
constexpr int SM_KST = 3 * STAGE;
constexpr int SM_Z = 131072;
constexpr int Z_Z3 = 6176, Z_CH = Z_Z3 + 4128;
constexpr int SM_WPHI = SM_Z + 47104;
constexpr int SM_ONES = SM_WPHI + 8192;
constexpr int SM_B = SM_ONES + 1024;
constexpr int U_CH = 4352, SM_ST = SM_B + 4 * U_CH;
constexpr int T_HH = 1280;
constexpr int SM_BAR = SM_ST + 4 * ST_SZ;
constexpr int SM_TOTAL = SM_BAR + 512;
static_assert(SM_TOTAL <= 232448 && SM_KST + 8 * ST_SZ <= SM_WPHI && SM_ST % 128 == 0, "smem");
#define stage_off(s) ((s) * STAGE)
constexpr int BAR_FULL = 0, BAR_FREE = 32  , BAR_SLAB = 72, BAR_KFREE = 80, BAR_RINGFREE = 96, BAR_WOLO = 104, BAR_WOHI = 112, BAR_KVDONE = 120, BAR_ODONE = 128, BAR_KVZ = 136, BAR_U = 144  , BAR_Z = 176  ;
#define FILL(s, f) do { mbar_expect_tx(bars + BAR_FULL + 8 * (s), STAGE); tma3d(sb + stage_off(s) + 16384, &mw, hg * 64, (f) * 64, 0, bars + BAR_FULL + 8 * (s)); \
                        tma2d(sb + stage_off(s), &mx, (f) * 64, rb * 128, bars + BAR_FULL + 8 * (s)); } while (0)
#define DSW(a, lbo) make_desc(a, lbo, 1024, 1)
#define NINIT 2
#define ODELAY 300
constexpr float LOG2E = 1.4426950408889634f;

__device__ __forceinline__ void dual_softmax16(const uint32_t* r, uint32_t* o) {
  const uint32_t m = bmax2(bmax2(bmax2(r[0], r[1]), bmax2(r[2], r[3])), bmax2(bmax2(r[4], r[5]), bmax2(r[6], r[7])));
  const uint32_t n = bmin2(bmin2(bmin2(r[0], r[1]), bmin2(r[2], r[3])), bmin2(bmin2(r[4], r[5]), bmin2(r[6], r[7])));
  const float mx = fmaxf(bf_lo(m), bf_hi(m)) * LOG2E, mn = fminf(bf_lo(n), bf_hi(n)) * LOG2E;
  float e[32];
#pragma unroll
  for (int i = 0; i < 16; i++) {
    const float v = (i & 1) ? bf_hi(r[i >> 1]) : bf_lo(r[i >> 1]);
    e[i] = ex2(fmaf(v, LOG2E, -mx)); e[16 + i] = ex2(fmaf(v, -LOG2E, mn));
  }
#pragma unroll
  for (int h = 0; h < 32; h += 16) {
    const float* x = e + h;
    const float sum = rcp((((x[0] + x[1]) + (x[2] + x[3])) + ((x[4] + x[5]) + (x[6] + x[7]))) + (((x[8] + x[9]) + (x[10] + x[11])) + ((x[12] + x[13]) + (x[14] + x[15]))));
#pragma unroll
    for (int i = 0; i < 8; i++) o[h / 2 + i] = pack_bf16(x[2 * i] * sum, x[2 * i + 1] * sum);
  }
}
__device__ __forceinline__ void reset_slots(uint4* p0, uint4* p1, uint32_t v) {
  asm volatile("{\n.reg .b128 t;\n.reg .b64 a;\nmov.b64 a, {%2,%2};\nmov.b128 t, {a,a};\n"
               "st.relaxed.gpu.global.b128 [%0], t;\nst.relaxed.gpu.global.b128 [%0+8192], t;\nst.relaxed.gpu.global.b128 [%1], t;\n"
               "st.relaxed.gpu.global.b128 [%1+512], t;\nst.relaxed.gpu.global.b128 [%1+1024], t;\nst.relaxed.gpu.global.b128 [%1+1536], t;\n}"
               :: "l"(p0), "l"(p1), "r"(v) : "memory");
}

struct Cx { float r, i; };
__device__ __forceinline__ Cx cmul(Cx a, Cx b) { return {fmaf(a.r, b.r, -a.i * b.i), fmaf(a.r, b.i, a.i * b.r)}; }
__device__ __forceinline__ Cx cmulc(Cx a, Cx b) { return {fmaf(a.r, b.r, a.i * b.i), fmaf(a.i, b.r, -a.r * b.i)}; }
__device__ __forceinline__ Cx cpow(float l2, float rh, float rl, float p) {
  float t = p * rh;
  float fr = t - ((t + 12582912.f) - 12582912.f);
  float ang = fmaf(p, rl, fr) * 6.283185307179586f;
  float m = ex2(l2 * p);
  return {m * __cosf(ang), m * __sinf(ang)};
}
__device__ __forceinline__ void toep(uint32_t addr, uint32_t* a) {
  a[1] = lds32(addr); a[3] = lds32(addr - 4); uint32_t x = lds32(addr - 8);
  a[0] = __byte_perm(a[1], a[3], 0x5432); a[2] = __byte_perm(a[3], x, 0x5432);
}

struct Params {
  const __nv_bfloat16 *x, *wqkv, *wo, *w_phi, *u, *log_a, *a_im, *c_re, *c_im, *log_dt, *d_skip;
  __nv_bfloat16* out;
};

__global__ void __launch_bounds__(512, 1)
fused_kernel(const __grid_constant__ CUtensorMap mx, const __grid_constant__ CUtensorMap mw, const __grid_constant__ CUtensorMap mo, const __grid_constant__ CUtensorMap mu, const Params prm) {
  extern __shared__ uint8_t smem_raw[];
  constexpr uint32_t sb = 1024;
  if (smem_u32(smem_raw) != sb) return;
  constexpr uint32_t bars = sb + SM_BAR;
#define PERM 0x3210
  const int tid = (threadIdx.x & 127) | (((PERM >> (4 * (threadIdx.x >> 7))) & 3) << 7), lane = tid & 31;
  const int cta = blockIdx.x, gi = cta >> 4;
  const int rb = (gi >> 1) * 4 + ((cta >> 2) & 3), hg = (gi & 1) * 4 + (cta & 3);
#define tag (ep + 1)
#define LOAD_EP(i) asm volatile("ld.global.u32 %0, [%1];" : "=r"(ep) : "l"(g_epoch + (i)))
  if (tid == 384) {
#pragma unroll
    for (int i = 0; i < 3; i++) mbar_init(bars + BAR_FULL + 8 * i, 1);
    mbar_init(bars + BAR_SLAB, 1);
    asm volatile("fence.mbarrier_init.release.cluster;" ::: "memory");
#pragma unroll
    for (int s = 0; s < 3; s++) { FILL(s, s);  }
  }
  const int d = cta * 4 + ((tid >> 5) & 3);
  uint2 la, ai, cr, ci; uint32_t ldt, dskb;
  if (tid < 256) {
    la = ldg64(prm.w_phi + hg * 1024 + tid * 4); asm volatile("ld.global.u32 %0, [%1];" : "=r"(ldt) : "l"(g_epoch + cta + (tid >> 10)));
  } else if (tid < 384) {
    la = ldg64(prm.log_a + d * 128 + lane * 4); ai = ldg64(prm.a_im + d * 128 + lane * 4);
    cr = ldg64(prm.c_re + d * 128 + lane * 4); ci = ldg64(prm.c_im + d * 128 + lane * 4);
    asm volatile("ld.global.nc.u16 %0, [%1];" : "=r"(ldt) : "l"(prm.log_dt + d));
    asm volatile("ld.global.nc.u16 %0, [%1];" : "=r"(dskb) : "l"(prm.d_skip + d));
  } else {
    if (tid == 480) {
      mbar_init(bars + BAR_KFREE, 4);
#pragma unroll
      for (int i = 0; i < 5; i++) mbar_init(bars + BAR_FREE + 8 * i, 2);
      mbar_init(bars + BAR_RINGFREE, 1); mbar_init(bars + BAR_WOLO, 1); mbar_init(bars + BAR_WOHI, 1);
      mbar_init(bars + BAR_KVDONE, 8); mbar_init(bars + BAR_ODONE, 8); mbar_init(bars + BAR_KVZ, 128);
#pragma unroll
      for (int i = 0; i < 8; i++) mbar_init(bars + BAR_U + 8 * i, 32);
      asm volatile("fence.mbarrier_init.release.cluster;" ::: "memory");
    }
    bar_sync(6, 128);
    asm volatile("bar.arrive 5, 512;" ::: "memory");
    asm volatile("setmaxnreg.dec.sync.aligned.u32 56;");
    TL(48, tid == 384);
    const int uw = __shfl_sync(~0u, (tid >> 5) & 3, 0), t = tid - 384, c = lane & 3;
    const uint32_t cb = sb + SM_B + uw * U_CH;
    uint32_t ep;
    int zit = 0;
    unsigned* fl = g_flag + (cta >> 2) * 32;
    {
      uint4 v[8];
      LOAD_EP(128 + cta * 4 + uw + (tid >> 10));
      if (t == 0) {
        mbar_wait(bars + BAR_FULL, 0);
        prefetch_l2((const char*)prm.wqkv + 192 * 3072 + cta * 7680, 7680);
        prefetch_l2((const char*)prm.x + (rb * 8 + hg) * 16384, 16384);
        mbar_expect_tx(bars + BAR_SLAB, 16384);
        tma2d(sb + SM_B, &mu, (cta >> 2) * 16, (cta & 3) * 512, bars + BAR_SLAB);
        tma2d(sb + SM_B + 8192, &mu, (cta >> 2) * 16, (cta & 3) * 512 + 256, bars + BAR_SLAB);
#pragma unroll 1
        for (int s = 0; s < 5; s++) { mbar_wait(bars + BAR_FREE + 8 * s, 0); FILL(s < 3 ? s : s - 3, s + 3); }
        prefetch_l2((const char*)prm.wo + cta * 4096, 4096);
      }
      __syncwarp();
      mbar_wait(bars + BAR_SLAB, 0);
#pragma unroll
      for (int i = 0; i < 8; i++) lds128(sb + SM_B + (t >> 1) * 256 + (t & 1) * 16 + i * 32, v[i].x, v[i].y, v[i].z, v[i].w);
      uint4* dst = g_ut + ((cta >> 2) * 16 + (t & 1) * 8) * 256 + (cta & 3) * 64 + (t >> 1);
      TL(26, t == 32 && v[0].x + v[7].x != 77);
#define TR(O, F, S) st_pkt(dst + O, __byte_perm(v[0].F, v[1].F, S), __byte_perm(v[2].F, v[3].F, S), __byte_perm(v[4].F, v[5].F, S), __byte_perm(v[6].F, v[7].F, S))
      TR(0, x, 0x5410); TR(256, x, 0x7632); TR(512, y, 0x5410); TR(768, y, 0x7632);
      TR(1024, z, 0x5410); TR(1280, z, 0x7632); TR(1536, w, 0x5410); TR(1792, w, 0x7632);
      TL(28, t == 0);
      if (uw < 3) asm volatile("bar.arrive 4, 128;" ::: "memory");
      else {
        bar_sync(4, 128);
        if (lane == 0) asm volatile("st.release.gpu.global.u32 [%0], %1;" :: "l"(fl + (cta & 3)), "r"(tag) : "memory");
        TL(19, t == 96);
      }
      uint32_t f; int it = 0;
#pragma unroll 1
      do { asm volatile("ld.acquire.gpu.global.u32 %0, [%1];" : "=r"(f) : "l"(fl + c) : "memory"); } while (f != tag && ++it < (1 << 16));
      __syncwarp();
      TL(27, t == 0);
      const uint4* src = g_ut + (cta * 4 + uw) * 256 + lane;
#pragma unroll
      for (int i = 0; i < 8; i++) v[i] = ld_pkt(src + i * 32);
#pragma unroll
      for (int i = 0; i < 8; i++) sts128(cb + 256 + (lane + 32 * i) * 16, v[i].x, v[i].y, v[i].z, v[i].w);
      if (lane < 16) sts128(cb + lane * 16, 0, 0, 0, 0);
      mbar_arrive(bars + BAR_U + 8 * uw);
      __syncwarp();
      TL(23, t == 0);
    }
    LOAD_EP(cta + (tid >> 10));
    if (lane < 8) st_pkt(g_kvf + hg * 512 + rb * 32 + uw * 8 + lane, ep, ep, ep, ep);
    const int wcol = (cta & 3) * 128 + (((uw >> 1) ^ uw) & 1) * 64, wrow = (uw >> 1) * 256;
    const uint32_t zc = sb + SM_Z + uw * Z_CH;
    mbar_wait(bars + BAR_RINGFREE, 0);
    if (uw == 3) mbar_wait(bars + BAR_KFREE, 0);
    if (lane == 0) {
      if (uw == 0) mbar_expect_tx(bars + BAR_WOLO, 65536);
      tma2d(sb + (4 + uw) * 16384, &mo, wcol, wrow, bars + BAR_WOLO);
      if (uw == 3) { mbar_expect_tx(bars + BAR_WOHI, 65536); tma2d(sb + 3 * 16384, &mo, wcol, wrow + 128, bars + BAR_WOHI); }
    }
    __syncwarp();
#pragma unroll 1
    for (int ph = 0; ph < 2; ph++) {
#pragma unroll 1
    for (; zit < 6; zit++) {
      if (ph == 0) {
        bool kv; int n = 0;
        while (!(kv = mbar_test(bars + BAR_KVDONE, 0)) && !mbar_try(bars + BAR_KFREE, 0) && ++n < (1 << 18)) {}
        if (kv) break;
      } else mbar_wait(bars + BAR_KFREE, 0);
      if (zit == 0 && lane < 3) sts128(zc + (lane == 2 ? Z_Z3 : lane * 16), 0, 0, 0, 0);
      uint32_t q[12];
      const uint32_t ua = cb + 256 - 32 + zit * 512 + lane * 16;
      lds128(ua, q[0], q[1], q[2], q[3]); lds128(ua + 16, q[4], q[5], q[6], q[7]); lds128(ua + 32, q[8], q[9], q[10], q[11]);
      float P[24];
      P[0] = 0.f; P[1] = bf_lo(q[0]);
#pragma unroll
      for (int k = 2; k < 24; k += 2) {
        P[k] = P[k - 2] + (bf_lo(q[k / 2 - 1]) + bf_hi(q[k / 2 - 1]));
        P[k + 1] = P[k] + bf_lo(q[k / 2]);
      }
      uint32_t z[8];
#pragma unroll
      for (int x = 0; x < 8; x++) z[x] = pack_bf16(P[14 + x] - P[11 + x], P[11 + x] - P[6 + x]);
      const uint32_t za = zc + zit * 1024 + lane * 32;
      sts128(za + 32, z[0], z[1], z[2], z[3]); sts128(za + 48, z[4], z[5], z[6], z[7]);
      if (zit < 4) {
#pragma unroll
        for (int x = 0; x < 8; x++) z[x] = pack_bf16(P[16 + x] - P[9 + x], P[9 + x] - P[x]);
        sts128(za + Z_Z3 + 16, z[0], z[1], z[2], z[3]); sts128(za + Z_Z3 + 32, z[4], z[5], z[6], z[7]);
      }
      if (zit == 5) { mbar_arrive(bars + BAR_Z + 8 * uw); TL(24, t == 0); }
    }
    if (ph) break;
    mbar_wait(bars + BAR_KVDONE, 0);
    TL(20, t == 0);
    {
      const uint4* src = g_kvp + ((hg * 16 + rb) * 16 + (lane >> 3) * 4) * 32 + uw * 8 + (lane & 7);
      float s0, s1, s2, s3, sz; int it = 0; bool ok;
#pragma unroll 1
      do {
        uint4 pk[4];
#pragma unroll
        for (int i = 0; i < 4; i++) pk[i] = ld_pkt(src + i * 32);
        ok = __all_sync(~0u, ((mism(pk[0].x, pk[1].x, tag) | mism(pk[2].x, pk[3].x, tag)) & 0xFF) == 0);
        s0 = s1 = s2 = s3 = sz = 0.f;
#pragma unroll
        for (int i = 0; i < 4; i++) {
          s0 += __uint_as_float(pk[i].x & ~0xFFu); s1 += __uint_as_float(pk[i].y); s2 += __uint_as_float(pk[i].z); s3 += __uint_as_float(pk[i].w);
          sz += __uint_as_float(__byte_perm(__byte_perm(pk[i].y, pk[i].z, 0x0400), pk[i].w, 0x4210));
        }
#pragma unroll
        for (int o = 8; o <= 16; o <<= 1) {
          s0 += __shfl_xor_sync(~0u, s0, o); s1 += __shfl_xor_sync(~0u, s1, o); s2 += __shfl_xor_sync(~0u, s2, o); s3 += __shfl_xor_sync(~0u, s3, o); sz += __shfl_xor_sync(~0u, sz, o);
        }
        if (ok && lane < 8) st_pkt(g_kvf + hg * 512 + rb * 32 + uw * 8 + lane, pack_bf16(s0, s1), pack_bf16(s2, s3), pack_bf16(sz, sz), tag);
      } while (!ok && ++it < (1 << 16));
    }
    TL(21, t == 0);
    {
      const uint4* src = g_kvf + hg * 512 + t;
      uint32_t bad; int it = 0;
#pragma unroll 1
      do {
        uint4 pk[4];
#pragma unroll
        for (int i = 0; i < 4; i++) pk[i] = ld_pkt(src + i * 128);
        bad = mism(pk[0].w, pk[1].w, tag) | mism(pk[2].w, pk[3].w, tag);
#pragma unroll
        for (int i = 0; i < 4; i++) {
          const uint32_t dst = sb + SM_V + (uw + 4 * i) * 384 + lane * 4;
          sts32(dst, pk[i].x); sts32(dst + 128, pk[i].y); sts32(dst + 256, pk[i].z);
        }
      } while (bad && ++it < (1 << 16));
      fence_async();
      mbar_arrive(bars + BAR_KVZ);
    }
    TL(22, t == 0);
    __syncwarp();
    }
    TL_DUMP(19, 28, t == 0);

    return;
  }
  const int warp = __shfl_sync(~0u, tid >> 5, 0);
  const int g = lane >> 2, c = lane & 3;
  bar_sync(5, 512);
  if (warp < 8) {
    asm volatile("setmaxnreg.inc.sync.aligned.u32 160;");
    TL(32, tid == 32);
    const int w = warp >> 2, wi = warp & 3;
    const uint32_t ep = ldt;
    uint4* const kvp_dst = g_kvp + ((hg * 16 + warp * 2) * 16 + rb) * 32 + lane;
    uint4* const o_dst = g_o + ((rb * 8 + warp) * 32 + hg * 4) * 32 + lane;
    float acc[96];
    int tr0 = 0, tr1 = 0;
    mbar_wait(bars + BAR_FULL, 0);
    TL(1, tid == 0);
    {
      int s = 0, ph = 0;
#pragma unroll 1
      for (int f = 0; f < 8; f++) {
        const uint32_t aa = sb + s * STAGE;
        wg_fence();
#pragma unroll
        for (int k = 0; k < 4; k++) wg_ss192(acc, DSW(aa + w * 8192 + k * 32, 16), DSW(aa + 16384 + k * 2048, 8192), (f | k) != 0);
        wg_commit();
        if (f == 7) break;
        if (++s == 3) { s = 0; ph ^= 1; }
        wg_wait<1>();
        if (f > 0 && f < 6 && (tid & 127) == 0) mbar_arrive(bars + BAR_FREE + 8 * (f - 1));
        if (f == 6) reset_slots(kvp_dst, o_dst, ep);
        mbar_wait(bars + BAR_FULL + 8 * s, ph);
      }
    }
    {
      const int h = warp >> 1, k = tid >> 2;
#pragma unroll
      for (int e = 0; e < 2; e++) {
        const uint32_t v = e ? la.y : la.x;
        sts128(sb + SM_WPHI + k * 128 + (((2 * c + e) ^ (k & 7)) << 4), h == 0 ? v : 0u, h == 1 ? v : 0u, h == 2 ? v : 0u, h == 3 ? v : 0u);
      }
      sts32(sb + SM_ONES + tid * 4, 0x3F803F80u);
      fence_async();
      bar_sync(1, 256);
    }
    wg_wait<0>();
    pin<96>(acc);
    TL(2, tid == 0);
    const int r16 = (lane & 7) + ((lane >> 3) & 1) * 8, sx = lane & 7, sch = lane >> 4;
    const uint32_t pka = sb + SM_PK + (c >> 1) * 16384 + (warp * 16 + g) * 128 + ((((c & 1) * 4) ^ g) << 4);
    uint32_t pr[16], qf[16];
    {
      float pp[32];
#pragma unroll
      for (int i = 0; i < 16; i++) { pr[i] = pack_bf16(acc[32 + 2 * i], acc[33 + 2 * i]); asm volatile("" : "+r"(pr[i])); }
      wg_fence();
#pragma unroll
      for (int h = 0; h < 4; h++) wg_rs64(pp, pr[4 * h], pr[4 * h + 1], pr[4 * h + 2], pr[4 * h + 3], DSW(sb + SM_WPHI + h * 2048, 8192), h != 0);
      wg_commit();
      bar_sync(1, 256);
      if (tid == 0) mbar_arrive(bars + BAR_RINGFREE);
#pragma unroll
      for (int h = 0; h < 4; h++)
        stsm4(sb + SM_V + (h >> 1) * 8192 + (warp * 16 + r16) * 64 + ((((h & 1) * 2 + sch) ^ (sx >> 1)) << 4), pack_bf16(acc[64 + 8 * h], acc[65 + 8 * h]), pack_bf16(acc[66 + 8 * h], acc[67 + 8 * h]),
              pack_bf16(acc[68 + 8 * h], acc[69 + 8 * h]), pack_bf16(acc[70 + 8 * h], acc[71 + 8 * h]));
#pragma unroll
      for (int i = 0; i < 16; i++) { qf[i] = pack_bf16(acc[2 * i], acc[2 * i + 1]); asm volatile("" : "+r"(qf[i])); }
      wg_wait<0>();
      pin<32>(pp);
#pragma unroll
      for (int i = 0; i < 8; i++) { pr[i] = pack_bf16(pp[4 * i], pp[4 * i + 1]); pr[8 + i] = pack_bf16(pp[4 * i + 2], pp[4 * i + 3]); }
    }
    TL(3, tid == 0);
#pragma unroll 1
    for (int pass = 0; pass < 2; pass++) {
      uint32_t o[32];
      dual_softmax16(pr, o); dual_softmax16(pr + 8, o + 16);
      if (pass) mbar_wait(bars + BAR_KVDONE, 0);
#pragma unroll
      for (int i = 0; i < 8; i++) sts128((pka ^ ((i & 3) * 16)) + (i >> 2) * 1024, o[4 * i], o[4 * i + 1], o[4 * i + 2], o[4 * i + 3]);
      fence_async();
      if (pass) break;
      bar_sync(1, 256);
      TL(4, tid == 0);
      float kv[40], pq[32];
      wg_fence();
#pragma unroll
      for (int k = 0; k < 8; k++) wg_tt40(kv + 20 * (k & 1), DSW(sb + SM_PK + w * 16384 + k * 2048, 8192), make_desc(sb + SM_V + w * 8192 + k * 1024, SM_ONES - SM_V - w * 8192 - k * 1024, 512, 2), k > 1);
      wg_commit();
#pragma unroll
      for (int h = 0; h < 4; h++) wg_rs64(pq, qf[4 * h], qf[4 * h + 1], qf[4 * h + 2], qf[4 * h + 3], DSW(sb + SM_WPHI + h * 2048, 8192), h != 0);
      wg_commit();
      wg_wait<1>();
      pin<40>(kv);
      const bool hi = wi >> 1;
#define KV(i) __float_as_uint(hi ? kv[8 + (i)] + kv[28 + (i)] : kv[i] + kv[20 + (i)])
#pragma unroll
      for (int half = 0; half < 2; half++) {
        const uint32_t zz = __float_as_uint(kv[16 + 2 * half] + kv[36 + 2 * half]);
        st_pkt(kvp_dst + half * 512, __byte_perm(KV(2 * half), tag, 0x3214), __byte_perm(KV(1 + 2 * half), zz, 0x3215), __byte_perm(KV(4 + 2 * half), zz, 0x3216), __byte_perm(KV(5 + 2 * half), zz, 0x3217));
      }
      if (lane == 0) mbar_arrive(bars + BAR_KVDONE);
      TL(5, tid == 0);
      wg_wait<0>();
      pin<32>(pq);
#pragma unroll
      for (int i = 0; i < 8; i++) { pr[i] = pack_bf16(pq[4 * i], pq[4 * i + 1]); pr[8 + i] = pack_bf16(pq[4 * i + 2], pq[4 * i + 3]); }
    }
    if (w) bar_sync(3, 128); else bar_sync(2, 128);
    TL(6, tid == 0);
    mbar_wait(bars + BAR_KVZ, 0);
    TL(7, tid == 0);
    {
      float nd[48];
      wg_fence();
#pragma unroll
      for (int h = 0; h < 4; h++) wg_ss24(nd + 12 * h, DSW(sb + SM_PK + w * 8192 + (h >> 1) * 16384 + (h & 1) * 64, 16), make_desc(sb + SM_V + h * 1536, 384, 128, 0), 0);
#pragma unroll
      for (int h = 0; h < 4; h++) wg_ss24(nd + 12 * h, DSW(sb + SM_PK + w * 8192 + (h >> 1) * 16384 + (h & 1) * 64 + 32, 16), make_desc(sb + SM_V + h * 1536 + 768, 384, 128, 0), 1);
      wg_commit();
      wg_wait<0>();
      pin<48>(nd);
      if (lane == 0) mbar_arrive(bars + BAR_ODONE);
#pragma unroll
      for (int h = 0; h < 4; h++) {
        const float* n = nd + 12 * h;
        float i0 = rcp(n[8] + 1e-6f), i1 = rcp(n[10] + 1e-6f);
        uint32_t o0 = pack_bf16(n[0] * i0, n[1] * i0), o1 = pack_bf16(n[2] * i1, n[3] * i1), o2 = pack_bf16(n[4] * i0, n[5] * i0), o3 = pack_bf16(n[6] * i1, n[7] * i1);
        st_pkt(o_dst + h * 32, (o0 & ~1u) | (tag & 1), o1, o2, o3);
      }
    }
    TL(8, tid == 0);
    if (lane == 0 && warp < 3) {
      mbar_wait(bars + BAR_ODONE, 0);
      tma2d(sb + warp * 16384, &mo, (cta & 3) * 128 + (((warp >> 1) ^ warp) & 1) * 64, (warp >> 1) * 256 + 128, bars + BAR_WOHI);
    }
    __syncwarp();
    const int rt = rb * 2 + (gi & 1), ct = cta & 3;
    {
      float o2[64];
      uint4 af[16];
      const uint4* src = g_o + ((rt * 4 + wi) * 32 + w * 16) * 32 + lane;
      mbar_wait(bars + BAR_WOLO, 0);
      if (ODELAY) __nanosleep(ODELAY);
#pragma unroll
      for (int i = 0; i < 16; i++) af[i] = ld_pkt(src + i * 32);
#define BADG(G) ((mism(af[4 * (G)].x, af[4 * (G) + 1].x, tag) | mism(af[4 * (G) + 2].x, af[4 * (G) + 3].x, tag)) & 1)
#pragma unroll
      for (int grp = 0; grp < 4; grp++) {
        uint4* a = af + 4 * grp;
#pragma unroll 1
        for (int it = 0; BADG(grp) && it < (1 << 16); it++) {
#pragma unroll
          for (int i = 0; i < 4; i++) a[i] = ld_pkt(src + (4 * grp + i) * 32);
#pragma unroll
          for (int g2 = grp + 1; g2 < 4; g2++) {
            const uint32_t bad = BADG(g2);
#pragma unroll
            for (int i = 0; i < 4; i++) ld_pkt_if(bad, af[4 * g2 + i], src + (4 * g2 + i) * 32);
          }
        }
        if (grp == 2) mbar_wait(bars + BAR_WOHI, 0);
        __syncwarp();
        TL(9, tid == 0 && grp == 0); TL(10, tid == 0 && grp == 3);
#pragma unroll
        for (int i = 0; i < 4; i++) asm volatile("and.b32 %0, %0, -2;" : "+r"(a[i].x));
        wg_fence();
#pragma unroll
        for (int i = 0; i < 4; i++) wg_rs128(o2, a[i].x, a[i].y, a[i].z, a[i].w, DSW(sb + (1 - (grp >> 1)) * 65536 + w * 32768 + (grp & 1) * 8192 + i * 2048, 16384), (grp | i) != 0);
        wg_commit();
      }
      wg_wait<0>();
      pin<64>(o2);
      TL(11, tid == 0);
      const uint32_t xs = sb + 65536 + (tid & 127) * 16;
#pragma unroll
      for (int i = 0; i < 8; i++)
        sts128(xs + w * 32768 + i * 2048, __float_as_uint(o2[32 + 4 * i]), __float_as_uint(o2[33 + 4 * i]), __float_as_uint(o2[34 + 4 * i]), __float_as_uint(o2[35 + 4 * i]));
      bar_sync(1, 256);
      const uint32_t ts = sb + 65536 + w * 32768 + 16384 + wi * 2048;
#pragma unroll
      for (int i = 0; i < 4; i++) {
        uint32_t x, y, z, t, ob[4];
#pragma unroll
        for (int e = 0; e < 2; e++) {
          lds128(xs + (w ^ 1) * 32768 + (2 * i + e) * 2048, x, y, z, t);
          const float* s0 = o2 + 8 * i + 4 * e;
          ob[2 * e] = pack_bf16(s0[0] + __uint_as_float(x), s0[1] + __uint_as_float(y));
          ob[2 * e + 1] = pack_bf16(s0[2] + __uint_as_float(z), s0[3] + __uint_as_float(t));
        }
        stsm4(ts + r16 * 128 + (((2 * i + sch) ^ sx) << 4), ob[0], ob[1], ob[2], ob[3]);
      }
      __syncwarp();
      __nv_bfloat16* op = prm.out + (size_t)(rt * 64 + wi * 16 + (lane >> 3)) * 1024 + ct * 128 + w * 64 + sx * 8;
#pragma unroll
      for (int i = 0; i < 4; i++) {
        const int r = i * 4 + (lane >> 3);
        uint32_t x, y, z, t; lds128(ts + r * 128 + ((sx ^ (r & 7)) << 4), x, y, z, t);
        *(uint4*)(op + i * 4096) = make_uint4(x, y, z, t);
      }
    }
    if (tid == 0) g_epoch[cta] = tag;
    TL(12, tid == 0); TL_DUMP(1, 12, tid == 0); TL_DUMP(29, 30, tid == 32); TL_DUMP(32, 32, tid == 32); TL_DUMP(40, 63, tid == 32);

  } else {
    asm volatile("setmaxnreg.inc.sync.aligned.u32 136;");
    TL(40, tid == 256);
    const int ch = warp & 3;
    const uint32_t cb = sb + SM_B + ch * U_CH, stg = sb + SM_ST + ch * ST_SZ;
    const float dt = bf_lo(pack_bf16(expf(bf_lo(ldt)), 0.f));
    TL(13, tid == 256 && dt > 0.f && la.x + ai.x + cr.x + ci.x != 12345);
    float kacc[6][4];
#pragma unroll
    for (int i = 0; i < 6; i++) { kacc[i][0] = kacc[i][1] = kacc[i][2] = kacc[i][3] = 0.f; }
#pragma unroll 1
    for (int step = 0; step < 8; step++) {
      const int bi = (0x02100210 >> (4 * step)) & 3;
      const uint32_t buf = bi ? sb + SM_KST + (ch * 2 + bi - 1) * ST_SZ : stg;
      if ((0x17 >> step) & 1) {
      const float ar = -bf_lo(pack_bf16(ex2(bf_lo(la.x) * LOG2E), 0.f)) * dt, th = bf_lo(ai.x) * dt;
      const float l2 = ar * LOG2E;
      const float rh = th * 0.15915494309189535f, rl = fmaf(th, 0.15915494309189535f, -rh) + th * 6.4206382e-09f;
      Cx e0 = {2.f * dt * bf_lo(cr.x), -2.f * dt * bf_lo(ci.x)};
      la.x = __funnelshift_r(la.x, la.y, 16); la.y >>= 16; ai.x = __funnelshift_r(ai.x, ai.y, 16); ai.y >>= 16;
      cr.x = __funnelshift_r(cr.x, cr.y, 16); cr.y >>= 16; ci.x = __funnelshift_r(ci.x, ci.y, 16); ci.y >>= 16;
      const Cx w1 = cpow(l2, rh, rl, 1.f), w8 = cpow(l2, rh, rl, 8.f), w64 = cpow(l2, rh, rl, 64.f), w256 = cpow(l2, rh, rl, 256.f);
      const uint32_t st = buf + lane * 4;
#define PUT(row, z) sts32((st ^ (((row) & 7) << 4)) + (row) * 128, pack_bf16((z).r, (z).i))
      Cx s[4]; s[0] = {1.f, 0.f}; s[1] = w64; s[2] = cmul(w64, w64); s[3] = cmul(s[2], w64);
#pragma unroll
      for (int i = 0; i < 8; i++) {
#pragma unroll
        for (int m = 0; m < 4; m++) {
          PUT(8 * m + i, s[m]);
          if (i < 7) s[m] = (m == 0 && i == 0) ? w8 : cmul(s[m], w8);
        }
      }
      Cx gq = e0, e4, t;
      PUT(32, e0);
#pragma unroll
      for (int j = 1; j < 8; j++) {
        gq = cmulc(gq, w1);
        PUT(32 + j, gq);
        if (j == 2 || j == 6) { t = cmulc(gq, w256); PUT(40 + j / 2, t); }
        if (j == 4) e4 = gq;
      }
      e4 = cmulc(e4, w256); PUT(42, e4);
      e4 = cmulc(e4, w256); PUT(45, e4);
      e4 = cmulc(e4, w256); PUT(47, e4);
#pragma unroll
      for (int q = 1; q <= 8; q++) { e0 = cmulc(e0, w256); PUT(q == 1 ? 40 : q == 2 ? 44 : q == 3 ? 46 : 44 + q, e0); }
      __syncwarp();
      } else {
      const uint32_t aa = buf + ((lane & 7) + ((lane >> 3) & 1) * 8) * 128 + (((lane >> 4) ^ (lane & 7)) << 4);
      const uint32_t ba = buf + (32 + (lane & 7)) * 128 + (((lane >> 3) ^ (lane & 7)) << 4);
#pragma unroll
      for (int kp = 0; kp < 2; kp++) {
        uint32_t b[3][4];
#pragma unroll
        for (int nt = 0; nt < 3; nt++) ldsm4((ba ^ (kp * 64)) + nt * 1024, b[nt][0], b[nt][1], b[nt][2], b[nt][3]);
#pragma unroll
        for (int k2 = 0; k2 < 2; k2++)
#pragma unroll
          for (int mt = 0; mt < 2; mt++) {
            uint32_t a0, a1, a2, a3; ldsm4((aa ^ (kp * 64 + k2 * 32)) + mt * 2048, a0, a1, a2, a3);
#pragma unroll
            for (int nt = 0; nt < 3; nt++) mma16816(kacc[mt * 3 + nt], a0, a1, a2, a3, b[nt][2 * k2], b[nt][2 * k2 + 1]);
          }
      }
      __syncwarp();
      }
      if (step == 6) { fence_async(); __syncwarp(); if (lane == 0) mbar_arrive(bars + BAR_KFREE); }
      TL(41 + step, tid == 256 && step < 7);
    }
    TL(14, tid == 256);
    const float dsk = bf_lo(dskb);
    {
      const uint32_t V = stg + 32;
      sts32(lane < 8 ? V - 32 + lane * 4 : V + (249 + lane) * 4, 0u);
      if (lane < 15) sts32(V + (281 + lane) * 4, 0u);
      __syncwarp();
      if (lane == 0) kacc[0][0] += dsk;
      const uint32_t h0 = c < 2 ? V + (127 + 2 * c) * 4 : stg + T_HH + (64 * (c - 2) - 1) * 2, h1 = c < 2 ? h0 + 10 : h0 + 2, hs = c < 2 ? 16 : 4;
#pragma unroll
      for (int mt = 0; mt < 2; mt++)
#pragma unroll
        for (int hf = 0; hf < 2; hf++) {
          const int i = 16 * mt + 8 * hf + g;
          sts32(V + (4 * i + c) * 4, pack_bf16(kacc[mt * 3][2 * hf + 1], kacc[mt * 3][2 * hf]));
          uint32_t v = pack_bf16(kacc[mt * 3 + 1][2 * hf], kacc[mt * 3 + 1][2 * hf + 1]);
          if (mt + hf > 0 || lane > 0) sts16(h0 + hs * i, v);
          sts16(h1 + hs * i, v >> 16);
          if (c < 2) sts32(h0 + 4 + hs * i, __byte_perm(v, v, 0x1010));
          if (mt + hf == 0 && lane == 2) { sts16(V + 255 * 4, v); sts32(V + 256 * 4, __byte_perm(v, v, 0x1010)); sts16(V + 257 * 4 + 2, v); }
          v = pack_bf16(kacc[mt * 3 + 2][2 * hf], kacc[mt * 3 + 2][2 * hf + 1]);
          sts16(stg + T_HH + (127 + 64 * c + i) * 2, v); sts16(stg + T_HH + (159 + 64 * c + i) * 2, v >> 16);
          if (mt + hf == 0 && lane == 0) { sts16(V + 281 * 4, v); sts16(V + 282 * 4 + 2, v); }
        }
      __syncwarp();
    }

    TL(15, tid == 256);
    mbar_wait(bars + BAR_U + 8 * ch, 0);
    float acc[16][4];
#pragma unroll
    for (int j = 0; j < 16; j++) { acc[j][0] = acc[j][1] = acc[j][2] = acc[j][3] = 0.f; }
    const uint32_t ub = cb + 256 + lane * 8;
    const uint32_t vb = stg + (8 + g - 2 * c) * 4;
    int trb = 0;
    {
      uint32_t a[4][4], bn[4];
#pragma unroll
      for (int q = 0; q < 4; q++) toep(vb + q * 256, a[q]);
      lds64(ub, bn[0], bn[1]); lds64(ub + 8 * 256, bn[2], bn[3]);
#pragma unroll 1
      for (int r = 0; r < 8; r++) {
        uint32_t an[4][4];
#pragma unroll
        for (int m = 0; m < 8; m++) {
          const uint32_t b0 = bn[0], b1 = bn[1], b2 = bn[2], b3 = bn[3];
          const uint32_t nx = m < 7 ? ub + (m + 1) * 256 - r * 32 : ub - (r + 1) * 32;
          lds64(nx, bn[0], bn[1]); lds64(nx + 8 * 256, bn[2], bn[3]);
          if (m >= 2 && m < 6) toep(vb + (m - 2) * 256 + (r + 1) * 32, an[m - 2]);
#pragma unroll
          for (int q = 0; q < 4; q++) {
            mma16816(acc[m + q], a[q][0], a[q][1], a[q][2], a[q][3], b0, b1);
            if (m + 8 + q < 16) mma16816(acc[m + 8 + q], a[q][0], a[q][1], a[q][2], a[q][3], b2, b3);
          }
        }
#pragma unroll
        for (int q = 0; q < 4; q++) { a[q][0] = an[q][0]; a[q][1] = an[q][1]; a[q][2] = an[q][2]; a[q][3] = an[q][3]; }
      }
    }
#pragma unroll 1
    for (int r = 0; r < 2; r++) {
      uint32_t a[2][4];
      toep(vb + (32 + r) * 32, a[0]); toep(vb + (35 + r) * 32, a[1]);
#pragma unroll
      for (int m = 0; m < 12; m++) {
        uint32_t b0, b1;
        lds64(ub + m * 256 - r * 32, b0, b1);
        mma16816(acc[m + 4], a[0][0], a[0][1], a[0][2], a[0][3], b0, b1);
        if (m < 8) mma16816(acc[m + 8], a[1][0], a[1][1], a[1][2], a[1][3], b0, b1);
      }
    }
    TL(16, tid == 256);
    uint32_t ep; LOAD_EP(128 + d + (tid >> 10));
    mbar_wait(bars + BAR_Z + 8 * ch, 0);
#pragma unroll 1
    for (int pi = 0; pi < 2; pi++) {
      uint32_t b[5][2];
      const int i0 = 65 - 8 * pi + 2 * g - c;
#pragma unroll
      for (int t = 0; t < 5; t++) {
        b[t][0] = lds32(stg + T_HH + (i0 - 16 * t) * 4); b[t][1] = lds32(stg + T_HH + (i0 - 16 * t - 4) * 4);
      }
      if (i0 > 63) b[0][0] = 0; if (i0 > 67) b[0][1] = 0;
      if (i0 < 64) b[4][0] = 0; if (i0 < 68) b[4][1] = 0;
      const uint32_t zb = sb + SM_Z + ch * Z_CH + (64 * pi + 8 * c + 2 * g) * 4;
#pragma unroll
      for (int k = 0; k < 12; k++) {
        uint32_t a0, a1, a2, a3;
        lds64(zb + k * 512, a0, a1); lds64(zb + k * 512 + 128, a2, a3);
#pragma unroll
        for (int t = 4; t >= 0; t--) if (8 - t + k < 16) mma16816(acc[8 - t + k], a0, a1, a2, a3, b[t][0], b[t][1]);
      }
    }
    {
      uint32_t b[8][2];
#pragma unroll
      for (int t = 0; t < 8; t++) { b[t][0] = lds32(stg + T_HH + (64 + 8 * t + g - c) * 4); b[t][1] = lds32(stg + T_HH + (60 + 8 * t + g - c) * 4); }
      if (g < c) b[0][0] = 0; if (g < c + 4) b[0][1] = 0;
      const uint32_t zb = sb + SM_Z + ch * Z_CH + Z_Z3 + (16 * c + 2 * g) * 4;
#pragma unroll
      for (int k = 0; k < 8; k++) {
        uint32_t a0, a1, a2, a3;
        lds64(zb + k * 512, a0, a1); lds64(zb + k * 512 + 256, a2, a3);
#pragma unroll
        for (int t = 0; t < 8 - k; t++) mma16816(acc[8 + k + t], a0, a1, a2, a3, b[t][0], b[t][1]);
      }
    }
    TL(17, tid == 256);
#pragma unroll
    for (int j = 0; j < 16; j += 2)
      st_pkt(g_y + (d * 8 + j / 2) * 32 + lane, (pack_bf16(acc[j][0], acc[j][2]) & ~1u) | (tag & 1), pack_bf16(acc[j][1], acc[j][3]),
             pack_bf16(acc[j + 1][0], acc[j + 1][2]), pack_bf16(acc[j + 1][1], acc[j + 1][3]));
    if (lane == 0) asm volatile("st.relaxed.gpu.global.u32 [%0], %1;" :: "l"(g_flag + (cta >> 2) * 32 + 16 + (d & 15)), "r"(tag) : "memory");
    {
      uint32_t f; int it = 0;
#pragma unroll 1
      do { asm volatile("ld.relaxed.gpu.global.u32 %0, [%1];" : "=r"(f) : "l"(g_flag + (cta >> 2) * 32 + 16 + (lane & 15)) : "memory"); } while (f != tag && ++it < (1 << 16));
      __syncwarp();
      const int jp = (cta & 3) * 2 + (ch >> 1), pos = (ch & 1) * 16 + (lane >> 1);
      const uint4* src = g_y + (((cta >> 2) * 16 + (lane & 1) * 8) * 8 + jp) * 32 + pos;
      __nv_bfloat16* op = prm.out + 512 + (cta >> 2) * 16 + (lane & 1) * 8 + (size_t)(256 * jp + 32 * (pos & 3) + 2 * (pos >> 2)) * 1024;
      uint4 v[8];
      it = 0;
#pragma unroll 1
      do {
#pragma unroll
        for (int i = 0; i < 8; i++) v[i] = ld_pkt(src + i * 256);
        f = mism(v[0].x, v[1].x, tag) | mism(v[2].x, v[3].x, tag) | mism(v[4].x, v[5].x, tag) | mism(v[6].x, v[7].x, tag);
      } while ((f & 1) && ++it < (1 << 16));
#define ROW(O, F, S, M) *(uint4*)(op + (O) * 1024) = make_uint4(__byte_perm(v[0].F, v[1].F, S) & M, __byte_perm(v[2].F, v[3].F, S) & M, __byte_perm(v[4].F, v[5].F, S) & M, __byte_perm(v[6].F, v[7].F, S) & M)
      ROW(0, x, 0x5410, 0xFFFEFFFEu); ROW(1, x, 0x7632, ~0u); ROW(16, y, 0x5410, ~0u); ROW(17, y, 0x7632, ~0u);
      ROW(128, z, 0x5410, ~0u); ROW(129, z, 0x7632, ~0u); ROW(144, w, 0x5410, ~0u); ROW(145, w, 0x7632, ~0u);
    }
    if (lane == 0) g_epoch[128 + d] = tag;
    TL(18, tid == 256); TL_DUMP(13, 18, tid == 256);

  }
}

typedef CUresult (*EncodeFn)(CUtensorMap*, CUtensorMapDataType, cuuint32_t, void*, const cuuint64_t*, const cuuint64_t*, const cuuint32_t*, const cuuint32_t*,
                             CUtensorMapInterleave, CUtensorMapSwizzle, CUtensorMapL2promotion, CUtensorMapFloatOOBfill);

extern "C" void kernel_launch(void* const* d_in, const int* in_sizes, int n_in, void* d_out, int out_size) {
  static bool init = false;
  static CUtensorMap mx, mw, mo, mu;
  if (!init) {
    void* fn = nullptr; cudaDriverEntryPointQueryResult qr;
    cudaGetDriverEntryPoint("cuTensorMapEncodeTiled", &fn, cudaEnableDefault, &qr);
    EncodeFn enc = (EncodeFn)fn;
    const cuuint32_t es[3] = {1, 1, 1};
    { cuuint64_t dims[2] = {512, 2048}, str[1] = {1024}; cuuint32_t box[2] = {64, 128};
      enc(&mx, CU_TENSOR_MAP_DATA_TYPE_BFLOAT16, 2, d_in[0], dims, str, box, es, CU_TENSOR_MAP_INTERLEAVE_NONE, CU_TENSOR_MAP_SWIZZLE_128B, CU_TENSOR_MAP_L2_PROMOTION_L2_128B, CU_TENSOR_MAP_FLOAT_OOB_FILL_NONE); }
    { cuuint64_t dims[3] = {512, 512, 3}, str[2] = {3072, 1024}; cuuint32_t box[3] = {64, 64, 3};
      enc(&mw, CU_TENSOR_MAP_DATA_TYPE_BFLOAT16, 3, d_in[1], dims, str, box, es, CU_TENSOR_MAP_INTERLEAVE_NONE, CU_TENSOR_MAP_SWIZZLE_128B, CU_TENSOR_MAP_L2_PROMOTION_L2_128B, CU_TENSOR_MAP_FLOAT_OOB_FILL_NONE); }
    { cuuint64_t dims[2] = {512, 512}, str[1] = {1024}; cuuint32_t box[2] = {64, 128};
      enc(&mo, CU_TENSOR_MAP_DATA_TYPE_BFLOAT16, 2, d_in[3], dims, str, box, es, CU_TENSOR_MAP_INTERLEAVE_NONE, CU_TENSOR_MAP_SWIZZLE_128B, CU_TENSOR_MAP_L2_PROMOTION_L2_128B, CU_TENSOR_MAP_FLOAT_OOB_FILL_NONE); }
    { cuuint64_t dims[2] = {512, 2048}, str[1] = {1024}; cuuint32_t box[2] = {16, 256};
      enc(&mu, CU_TENSOR_MAP_DATA_TYPE_BFLOAT16, 2, d_in[4], dims, str, box, es, CU_TENSOR_MAP_INTERLEAVE_NONE, CU_TENSOR_MAP_SWIZZLE_NONE, CU_TENSOR_MAP_L2_PROMOTION_L2_128B, CU_TENSOR_MAP_FLOAT_OOB_FILL_NONE); }
    cudaFuncSetAttribute(fused_kernel, cudaFuncAttributeMaxDynamicSharedMemorySize, SM_TOTAL);
    init = true;
  }
  Params p;
  p.x = (const __nv_bfloat16*)d_in[0]; p.wqkv = (const __nv_bfloat16*)d_in[1]; p.wo = (const __nv_bfloat16*)d_in[3];
  p.w_phi = (const __nv_bfloat16*)d_in[2]; p.u = (const __nv_bfloat16*)d_in[4]; p.log_a = (const __nv_bfloat16*)d_in[5]; p.a_im = (const __nv_bfloat16*)d_in[6];
  p.c_re = (const __nv_bfloat16*)d_in[7]; p.c_im = (const __nv_bfloat16*)d_in[8]; p.log_dt = (const __nv_bfloat16*)d_in[9]; p.d_skip = (const __nv_bfloat16*)d_in[10];
  p.out = (__nv_bfloat16*)d_out;
  fused_kernel<<<128, 512, SM_TOTAL, cudaStreamPerThread>>>(mx, mw, mo, mu, p);
}
```

```cpp
#include <cuda_runtime.h>
#include <cuda_bf16.h>
#include <cuda_fp16.h>
#include <cuda.h>
#include <stdint.h>

__device__ uint4 g_kvp[8 * 16 * 16 * 32];
__device__ uint4 g_kvf[8 * 512];
__device__ uint4 g_o[128 * 32 * 32];
__device__ uint4 g_y[512 * 8 * 32];
__device__ unsigned g_epoch[128 + 512];

__device__ __forceinline__ uint32_t smem_u32(const void* p) { return (uint32_t)__cvta_generic_to_shared(p); }
__device__ __forceinline__ void mbar_init(uint32_t bar, uint32_t cnt) { asm volatile("mbarrier.init.shared::cta.b64 [%0], %1;" :: "r"(bar), "r"(cnt)); }
__device__ __forceinline__ void mbar_expect_tx(uint32_t bar, uint32_t bytes) { asm volatile("mbarrier.arrive.expect_tx.shared::cta.b64 _, [%0], %1;" :: "r"(bar), "r"(bytes) : "memory"); }
__device__ __forceinline__ void mbar_arrive(uint32_t bar) { asm volatile("mbarrier.arrive.shared::cta.b64 _, [%0];" :: "r"(bar) : "memory"); }
__device__ __forceinline__ void mbar_wait(uint32_t bar, uint32_t parity) {
  asm volatile("{\n.reg .pred p, q;\n.reg .u32 n;\nmbarrier.try_wait.parity.shared::cta.b64 p, [%0], %1;\n@p bra D_%=;\nmov.u32 n, 0;\n"
               "W_%=:\nmbarrier.try_wait.parity.shared::cta.b64 p, [%0], %1, 4000;\nadd.u32 n, n, 1;\nsetp.lt.and.u32 q, n, 65536, !p;\n@q bra W_%=;\nD_%=:\n}" :: "r"(bar), "r"(parity) : "memory");
}
__device__ __forceinline__ void slice(uint32_t& kb) {
  asm volatile("{\n.reg .pred p, q;\n.reg .u32 n;\nmbarrier.test_wait.parity.shared::cta.b64 p, [%0], 0;\n@!p bra.uni S_%=;\nmov.u32 n, 0;\n"
               "W_%=:\nmbarrier.try_wait.parity.shared::cta.b64 p, [%0+24], 0, 4000;\nadd.u32 n, n, 1;\nsetp.lt.and.u32 q, n, 65536, !p;\n@q bra.uni W_%=;\n"
               "add.u32 %0, %0, 16;\nS_%=:\n}" : "+r"(kb) :: "memory");
}
#define bar_arrive(id, n) asm volatile("bar.arrive " #id ", " #n ";" ::: "memory")
#define bar_sync(id, n) asm volatile("bar.sync " #id ", " #n ";" ::: "memory")
__device__ __forceinline__ void fence_async() { asm volatile("fence.proxy.async.shared::cta;" ::: "memory"); }
__device__ __forceinline__ void tma2d(uint32_t dst, const CUtensorMap* m, int c0, int c1, uint32_t bar) {
  asm volatile("cp.async.bulk.tensor.2d.shared::cluster.global.mbarrier::complete_tx::bytes [%0], [%1, {%3, %4}], [%2];" :: "r"(dst), "l"(m), "r"(bar), "r"(c0), "r"(c1) : "memory");
}
__device__ __forceinline__ void tma3d(uint32_t dst, const CUtensorMap* m, int c0, int c1, int c2, uint32_t bar) {
  asm volatile("cp.async.bulk.tensor.3d.shared::cluster.global.mbarrier::complete_tx::bytes [%0], [%1, {%3, %4, %5}], [%2];" :: "r"(dst), "l"(m), "r"(bar), "r"(c0), "r"(c1), "r"(c2) : "memory");
}
__device__ __forceinline__ uint64_t make_desc(uint32_t addr, uint32_t lbo, uint32_t sbo, int swz) {
  const uint32_t lo = (addr >> 4) + ((lbo >> 4) << 16), hi = (sbo >> 4) | ((uint32_t)swz << 30);
  uint64_t d; asm("mov.b64 %0, {%1,%2};" : "=l"(d) : "r"(lo), "r"(hi)); return d;
}
__device__ __forceinline__ void wg_fence() { asm volatile("wgmma.fence.sync.aligned;" ::: "memory"); }
__device__ __forceinline__ void wg_commit() { asm volatile("wgmma.commit_group.sync.aligned;" ::: "memory"); }
template <int N> __device__ __forceinline__ void wg_wait() { asm volatile("wgmma.wait_group.sync.aligned %0;" :: "n"(N) : "memory"); }
template <int N> __device__ __forceinline__ void pin(float* d) {
#pragma unroll
  for (int i = 0; i < N; i++) asm volatile("" : "+f"(d[i]) :: "memory");
}
__device__ __forceinline__ void wg_ss192(float* d, uint64_t da, uint64_t db, int sd) {
  asm volatile("{\n.reg .pred p;\nsetp.ne.b32 p, %98, 0;\nwgmma.mma_async.sync.aligned.m64n192k16.f32.bf16.bf16 {%0,%1,%2,%3,%4,%5,%6,%7,%8,%9,%10,%11,%12,%13,%14,%15,%16,%17,%18,%19,%20,%21,%22,%23,%24,%25,%26,%27,%28,%29,%30,%31,%32,%33,%34,%35,%36,%37,%38,%39,%40,%41,%42,%43,%44,%45,%46,%47,%48,%49,%50,%51,%52,%53,%54,%55,%56,%57,%58,%59,%60,%61,%62,%63,%64,%65,%66,%67,%68,%69,%70,%71,%72,%73,%74,%75,%76,%77,%78,%79,%80,%81,%82,%83,%84,%85,%86,%87,%88,%89,%90,%91,%92,%93,%94,%95}, %96, %97, p, 1, 1, 0, 1;\n}"
    : "+f"(d[0]),"+f"(d[1]),"+f"(d[2]),"+f"(d[3]),"+f"(d[4]),"+f"(d[5]),"+f"(d[6]),"+f"(d[7]),"+f"(d[8]),"+f"(d[9]),"+f"(d[10]),"+f"(d[11]),"+f"(d[12]),"+f"(d[13]),"+f"(d[14]),"+f"(d[15]),"+f"(d[16]),"+f"(d[17]),"+f"(d[18]),"+f"(d[19]),"+f"(d[20]),"+f"(d[21]),"+f"(d[22]),"+f"(d[23]),"+f"(d[24]),"+f"(d[25]),"+f"(d[26]),"+f"(d[27]),"+f"(d[28]),"+f"(d[29]),"+f"(d[30]),"+f"(d[31]),"+f"(d[32]),"+f"(d[33]),"+f"(d[34]),"+f"(d[35]),"+f"(d[36]),"+f"(d[37]),"+f"(d[38]),"+f"(d[39]),"+f"(d[40]),"+f"(d[41]),"+f"(d[42]),"+f"(d[43]),"+f"(d[44]),"+f"(d[45]),"+f"(d[46]),"+f"(d[47]),"+f"(d[48]),"+f"(d[49]),"+f"(d[50]),"+f"(d[51]),"+f"(d[52]),"+f"(d[53]),"+f"(d[54]),"+f"(d[55]),"+f"(d[56]),"+f"(d[57]),"+f"(d[58]),"+f"(d[59]),"+f"(d[60]),"+f"(d[61]),"+f"(d[62]),"+f"(d[63]),"+f"(d[64]),"+f"(d[65]),"+f"(d[66]),"+f"(d[67]),"+f"(d[68]),"+f"(d[69]),"+f"(d[70]),"+f"(d[71]),"+f"(d[72]),"+f"(d[73]),"+f"(d[74]),"+f"(d[75]),"+f"(d[76]),"+f"(d[77]),"+f"(d[78]),"+f"(d[79]),"+f"(d[80]),"+f"(d[81]),"+f"(d[82]),"+f"(d[83]),"+f"(d[84]),"+f"(d[85]),"+f"(d[86]),"+f"(d[87]),"+f"(d[88]),"+f"(d[89]),"+f"(d[90]),"+f"(d[91]),"+f"(d[92]),"+f"(d[93]),"+f"(d[94]),"+f"(d[95]) : "l"(da), "l"(db), "r"(sd));
}
__device__ __forceinline__ void wg_ss24(float* d, uint64_t da, uint64_t db, int sd) {
  asm volatile("{\n.reg .pred p;\nsetp.ne.b32 p, %14, 0;\nwgmma.mma_async.sync.aligned.m64n24k16.f32.bf16.bf16 {%0,%1,%2,%3,%4,%5,%6,%7,%8,%9,%10,%11}, %12, %13, p, 1, 1, 0, 1;\n}"
    : "+f"(d[0]),"+f"(d[1]),"+f"(d[2]),"+f"(d[3]),"+f"(d[4]),"+f"(d[5]),"+f"(d[6]),"+f"(d[7]),"+f"(d[8]),"+f"(d[9]),"+f"(d[10]),"+f"(d[11]) : "l"(da), "l"(db), "r"(sd));
}
__device__ __forceinline__ void wg_tt40(float* d, uint64_t da, uint64_t db, int sd) {
  asm volatile("{\n.reg .pred p;\nsetp.ne.b32 p, %22, 0;\nwgmma.mma_async.sync.aligned.m64n40k16.f32.bf16.bf16 {%0,%1,%2,%3,%4,%5,%6,%7,%8,%9,%10,%11,%12,%13,%14,%15,%16,%17,%18,%19}, %20, %21, p, 1, 1, 1, 1;\n}"
    : "+f"(d[0]),"+f"(d[1]),"+f"(d[2]),"+f"(d[3]),"+f"(d[4]),"+f"(d[5]),"+f"(d[6]),"+f"(d[7]),"+f"(d[8]),"+f"(d[9]),"+f"(d[10]),"+f"(d[11]),"+f"(d[12]),"+f"(d[13]),"+f"(d[14]),"+f"(d[15]),"+f"(d[16]),"+f"(d[17]),"+f"(d[18]),"+f"(d[19]) : "l"(da), "l"(db), "r"(sd));
}
__device__ __forceinline__ void wg_rs64(float* d, uint32_t a0, uint32_t a1, uint32_t a2, uint32_t a3, uint64_t db, int sd) {
  asm volatile("{\n.reg .pred p;\nsetp.ne.b32 p, %37, 0;\nwgmma.mma_async.sync.aligned.m64n64k16.f32.bf16.bf16 {%0,%1,%2,%3,%4,%5,%6,%7,%8,%9,%10,%11,%12,%13,%14,%15,%16,%17,%18,%19,%20,%21,%22,%23,%24,%25,%26,%27,%28,%29,%30,%31}, {%32,%33,%34,%35}, %36, p, 1, 1, 1;\n}"
    : "+f"(d[0]),"+f"(d[1]),"+f"(d[2]),"+f"(d[3]),"+f"(d[4]),"+f"(d[5]),"+f"(d[6]),"+f"(d[7]),"+f"(d[8]),"+f"(d[9]),"+f"(d[10]),"+f"(d[11]),"+f"(d[12]),"+f"(d[13]),"+f"(d[14]),"+f"(d[15]),"+f"(d[16]),"+f"(d[17]),"+f"(d[18]),"+f"(d[19]),"+f"(d[20]),"+f"(d[21]),"+f"(d[22]),"+f"(d[23]),"+f"(d[24]),"+f"(d[25]),"+f"(d[26]),"+f"(d[27]),"+f"(d[28]),"+f"(d[29]),"+f"(d[30]),"+f"(d[31]) : "r"(a0), "r"(a1), "r"(a2), "r"(a3), "l"(db), "r"(sd));
}
__device__ __forceinline__ void mma16816(float* c, uint32_t a0, uint32_t a1, uint32_t a2, uint32_t a3, uint32_t b0, uint32_t b1) {
  asm volatile("mma.sync.aligned.m16n8k16.row.col.f32.bf16.bf16.f32 {%0,%1,%2,%3}, {%4,%5,%6,%7}, {%8,%9}, {%0,%1,%2,%3};"
    : "+f"(c[0]), "+f"(c[1]), "+f"(c[2]), "+f"(c[3]) : "r"(a0), "r"(a1), "r"(a2), "r"(a3), "r"(b0), "r"(b1));
}
__device__ __forceinline__ uint32_t pack_bf16(float lo, float hi) { uint32_t r; asm("cvt.rn.bf16x2.f32 %0, %1, %2;" : "=r"(r) : "f"(hi), "f"(lo)); return r; }
__device__ __forceinline__ float bf_lo(uint32_t v) { return __uint_as_float(v << 16); }
__device__ __forceinline__ float bf_hi(uint32_t v) { return __uint_as_float(v & 0xFFFF0000u); }
__device__ __forceinline__ uint32_t bmax2(uint32_t a, uint32_t b) { uint32_t r; asm("max.bf16x2 %0, %1, %2;" : "=r"(r) : "r"(a), "r"(b)); return r; }
__device__ __forceinline__ uint32_t bmin2(uint32_t a, uint32_t b) { uint32_t r; asm("min.bf16x2 %0, %1, %2;" : "=r"(r) : "r"(a), "r"(b)); return r; }
__device__ __forceinline__ float ex2(float x) { float r; asm("ex2.approx.ftz.f32 %0, %1;" : "=f"(r) : "f"(x)); return r; }
__device__ __forceinline__ float rcp(float x) { float r; asm("rcp.approx.ftz.f32 %0, %1;" : "=f"(r) : "f"(x)); return r; }
__device__ __forceinline__ void stsm4(uint32_t addr, uint32_t r0, uint32_t r1, uint32_t r2, uint32_t r3) {
  asm volatile("stmatrix.sync.aligned.m8n8.x4.shared.b16 [%0], {%1,%2,%3,%4};" :: "r"(addr), "r"(r0), "r"(r1), "r"(r2), "r"(r3) : "memory");
}
__device__ __forceinline__ void ldsm4(uint32_t addr, uint32_t& r0, uint32_t& r1, uint32_t& r2, uint32_t& r3) {
  asm volatile("ldmatrix.sync.aligned.m8n8.x4.shared.b16 {%0,%1,%2,%3}, [%4];" : "=r"(r0), "=r"(r1), "=r"(r2), "=r"(r3) : "r"(addr) : "memory");
}
__device__ __forceinline__ void ldsm4t(uint32_t addr, uint32_t& r0, uint32_t& r1, uint32_t& r2, uint32_t& r3) {
  asm volatile("ldmatrix.sync.aligned.m8n8.x4.trans.shared.b16 {%0,%1,%2,%3}, [%4];" : "=r"(r0), "=r"(r1), "=r"(r2), "=r"(r3) : "r"(addr) : "memory");
}
__device__ __forceinline__ void sts32(uint32_t a, uint32_t v) { asm volatile("st.shared.b32 [%0], %1;" :: "r"(a), "r"(v) : "memory"); }
__device__ __forceinline__ void sts16(uint32_t a, uint32_t v) { asm volatile("st.shared.b16 [%0], %1;" :: "r"(a), "h"((uint16_t)v) : "memory"); }
__device__ __forceinline__ void sts64(uint32_t a, uint32_t x, uint32_t y) { asm volatile("st.shared.v2.b32 [%0], {%1,%2};" :: "r"(a), "r"(x), "r"(y) : "memory"); }
__device__ __forceinline__ void sts128(uint32_t a, uint32_t x, uint32_t y, uint32_t z, uint32_t w) { asm volatile("st.shared.v4.b32 [%0], {%1,%2,%3,%4};" :: "r"(a), "r"(x), "r"(y), "r"(z), "r"(w) : "memory"); }
__device__ __forceinline__ uint32_t lds32(uint32_t a) { uint32_t v; asm volatile("ld.shared.b32 %0, [%1];" : "=r"(v) : "r"(a) : "memory"); return v; }
__device__ __forceinline__ void lds64(uint32_t a, uint32_t& x, uint32_t& y) { asm volatile("ld.shared.v2.b32 {%0,%1}, [%2];" : "=r"(x), "=r"(y) : "r"(a) : "memory"); }
__device__ __forceinline__ void lds128(uint32_t a, uint32_t& x, uint32_t& y, uint32_t& z, uint32_t& w) { asm volatile("ld.shared.v4.b32 {%0,%1,%2,%3}, [%4];" : "=r"(x), "=r"(y), "=r"(z), "=r"(w) : "r"(a) : "memory"); }
__device__ __forceinline__ uint4 ld_pkt(const uint4* p) {
  uint4 v;
  asm volatile("{\n.reg .b128 t;\n.reg .b64 a, b;\nld.relaxed.gpu.global.b128 t, [%4];\nmov.b128 {a,b}, t;\nmov.b64 {%0,%1}, a;\nmov.b64 {%2,%3}, b;\n}"
               : "=r"(v.x), "=r"(v.y), "=r"(v.z), "=r"(v.w) : "l"(p) : "memory");
  return v;
}
__device__ __forceinline__ void st_pkt(uint4* p, uint32_t x, uint32_t y, uint32_t z, uint32_t w) {
  asm volatile("{\n.reg .b128 t;\n.reg .b64 a, b;\nmov.b64 a, {%0,%1};\nmov.b64 b, {%2,%3};\nmov.b128 t, {a,b};\nst.relaxed.gpu.global.b128 [%4], t;\n}"
               :: "r"(x), "r"(y), "r"(z), "r"(w), "l"(p) : "memory");
}
__device__ __forceinline__ void stg128(void* p, uint32_t x, uint32_t y, uint32_t z, uint32_t w) { asm volatile("st.global.v4.b32 [%0], {%1,%2,%3,%4};" :: "l"(p), "r"(x), "r"(y), "r"(z), "r"(w) : "memory"); }
__device__ __forceinline__ uint2 ldg64(const void* p) { uint2 v; asm volatile("ld.global.nc.v2.b32 {%0,%1}, [%2];" : "=r"(v.x), "=r"(v.y) : "l"(p)); return v; }

__device__ __forceinline__ uint32_t mism(uint32_t a, uint32_t b, uint32_t t) { uint32_t r; asm("lop3.b32 %0, %1, %2, %3, 0x7E;" : "=r"(r) : "r"(a), "r"(b), "r"(t)); return r; }
__device__ __forceinline__ void prefetch_l2(const void* p, uint32_t bytes) { asm volatile("cp.async.bulk.prefetch.L2.global [%0], %1;" :: "l"(p), "r"(bytes)); }

constexpr int STAGE = 40960;
constexpr int SM_PK = 65536;
constexpr int SM_V = 98304;
constexpr int SM_WPHI = 114688;
constexpr int ST_SZ = 53 * 128;
constexpr int SM_LAND = 3 * STAGE;
constexpr int SM_Z = SM_LAND + 16384;
constexpr int Z_Z3 = 6208, Z_CH = 10368;
constexpr int SM_ONES = SM_Z + 4 * Z_CH;
constexpr int SM_B = SM_ONES + 1024;
constexpr int U_CH = 4368, SM_ST = SM_B + 17536 + 256;
constexpr int T_HH = 64, T_V = 1024;
constexpr int SM_BAR = SM_ST + 4 * ST_SZ;
constexpr int SM_TOTAL = SM_BAR + 1024;
static_assert(SM_TOTAL <= 232448 && SM_ST % 128 == 0, "smem");
constexpr int BAR_FULL = 0, BAR_FREE = 32  , BAR_SLAB = 208  , BAR_KREQ = 272  , BAR_KDONE = 296  , BAR_WOLO = 104, BAR_WOHI = 112;
#define FILL(s, f) do { mbar_expect_tx(bars + BAR_FULL + 8 * (s), STAGE); tma3d(sb + (s) * STAGE + 16384, &mw, hg * 64, (f) * 64, 0, bars + BAR_FULL + 8 * (s)); \
                        tma2d(sb + (s) * STAGE, &mx, (f) * 64, rb * 128, bars + BAR_FULL + 8 * (s)); } while (0)
#define DSW(a, lbo) make_desc(a, lbo, 1024, 1)
constexpr int NFL = 4;
constexpr int ODELAY = 400;
constexpr int GPACE = 50;
constexpr int YDELAY = 250;
constexpr int KSPLIT = 6;
constexpr float LOG2E = 1.4426950408889634f;

__device__ __forceinline__ void dual_softmax2(const uint32_t* r, uint32_t* o) {
  float ref[4], inv[4];
#pragma unroll
  for (int h = 0; h < 2; h++) {
    const uint32_t* q = r + 8 * h;
    const uint32_t m = bmax2(bmax2(bmax2(q[0], q[1]), bmax2(q[2], q[3])), bmax2(bmax2(q[4], q[5]), bmax2(q[6], q[7])));
    const uint32_t n = bmin2(bmin2(bmin2(q[0], q[1]), bmin2(q[2], q[3])), bmin2(bmin2(q[4], q[5]), bmin2(q[6], q[7])));
    ref[2 * h] = -fmaxf(bf_lo(m), bf_hi(m)) * LOG2E; ref[2 * h + 1] = fminf(bf_lo(n), bf_hi(n)) * LOG2E;
  }
#pragma unroll
  for (int gp = 0; gp < 4; gp++) {
    const uint32_t* q = r + 8 * (gp >> 1);
    if (gp >= 1) ref[gp] = fmaf(inv[gp - 1], 0.f, ref[gp]);
    float x[16];
#pragma unroll
    for (int i = 0; i < 16; i++) x[i] = ex2(fmaf((i & 1) ? bf_hi(q[i >> 1]) : bf_lo(q[i >> 1]), (gp & 1) ? -LOG2E : LOG2E, ref[gp]));
    inv[gp] = rcp((((x[0] + x[1]) + (x[2] + x[3])) + ((x[4] + x[5]) + (x[6] + x[7]))) + (((x[8] + x[9]) + (x[10] + x[11])) + ((x[12] + x[13]) + (x[14] + x[15]))));
#pragma unroll
    for (int i = 0; i < 8; i++) o[8 * gp + i] = pack_bf16(x[2 * i] * inv[gp], x[2 * i + 1] * inv[gp]);
  }
}

struct Cx { float r, i; };
__device__ __forceinline__ Cx cmul(Cx a, Cx b) { return {fmaf(a.r, b.r, -a.i * b.i), fmaf(a.r, b.i, a.i * b.r)}; }
__device__ __forceinline__ Cx cmulc(Cx a, Cx b) { return {fmaf(a.r, b.r, a.i * b.i), fmaf(a.i, b.r, -a.r * b.i)}; }
__device__ __forceinline__ Cx cpow(float l2, float rh, float rl, float p) {
  float t = p * rh;
  float fr = t - ((t + 12582912.f) - 12582912.f);
  float ang = fmaf(p, rl, fr) * 6.283185307179586f;
  float m = ex2(l2 * p);
  return {m * __cosf(ang), m * __sinf(ang)};
}
__device__ __forceinline__ Cx csqr(Cx a) { return {fmaf(a.r, a.r, -a.i * a.i), 2.f * a.r * a.i}; }
__device__ __forceinline__ uint32_t pack_h(float lo, float hi) { uint32_t r; asm("cvt.rn.f16x2.f32 %0, %1, %2;" : "=r"(r) : "f"(hi), "f"(lo)); return r; }
__device__ __forceinline__ uint32_t hcmul(uint32_t a, uint32_t b, uint32_t bp) {
  const __half2 x = *(__half2*)&a;
  const __half2 z = __hfma2(__high2half2(x), *(__half2*)&bp, __hmul2(__low2half2(x), *(__half2*)&b));
  return *(const uint32_t*)&z;
}
__device__ __forceinline__ void mma16816h(float* c, const uint32_t* a, uint32_t b0, uint32_t b1) {
  asm volatile("mma.sync.aligned.m16n8k16.row.col.f32.f16.f16.f32 {%0,%1,%2,%3}, {%4,%5,%6,%7}, {%8,%9}, {%0,%1,%2,%3};"
    : "+f"(c[0]), "+f"(c[1]), "+f"(c[2]), "+f"(c[3]) : "r"(a[0]), "r"(a[1]), "r"(a[2]), "r"(a[3]), "r"(b0), "r"(b1));
}

struct Params {
  const __nv_bfloat16 *log_a, *a_im, *c_re, *c_im, *log_dt, *d_skip, *w_phi, *x, *wqkv, *wo, *u;
  __nv_bfloat16* out;
};

__global__ void __launch_bounds__(512, 1)
fused_kernel(const Params prm, const __grid_constant__ CUtensorMap mx, const __grid_constant__ CUtensorMap mw, const __grid_constant__ CUtensorMap mo, const __grid_constant__ CUtensorMap mu) {
  extern __shared__ uint8_t smem_raw[];
  constexpr uint32_t sb = 1024;
  if (smem_u32(smem_raw) != sb) return;
  constexpr uint32_t bars = sb + SM_BAR;
  const int tid = threadIdx.x, lane = tid & 31;
  const int cta = blockIdx.x, gi = cta >> 4;
  const int rb = (gi >> 1) * 4 + ((cta >> 2) & 3), hg = (gi & 1) * 4 + (cta & 3);
#define tag (ep + 1)
#define LOAD_EP(i) asm volatile("ld.global.u32 %0, [%1];" : "=r"(ep) : "l"(g_epoch + (i)))
  const int d = cta * 4 + ((tid >> 5) & 3);
  uint2 la, ai, cr, ci; uint32_t ldt, dskb;
  if ((tid >> 7) == 2) {
    la = ldg64(prm.log_a + d * 128 + lane * 4); ai = ldg64(prm.a_im + d * 128 + lane * 4);
    cr = ldg64(prm.c_re + d * 128 + lane * 4); ci = ldg64(prm.c_im + d * 128 + lane * 4);
    asm volatile("ld.global.nc.u16 %0, [%1];" : "=r"(ldt) : "l"(prm.log_dt + d));
    asm volatile("ld.global.nc.u16 %0, [%1];" : "=r"(dskb) : "l"(prm.d_skip + d));
  }
  if (tid == 384) {
#pragma unroll
    for (int i = 0; i < 3; i++) mbar_init(bars + BAR_FULL + 8 * i, 1);
    asm volatile("fence.mbarrier_init.release.cluster;" ::: "memory");
#pragma unroll 1
    for (int s = 0; s < 3; s++) FILL(s, s);
  }
  if (tid >= 384) {
    if (tid == 480) {
#pragma unroll
      for (int i = 0; i < 6; i++) mbar_init(bars + BAR_FREE + 8 * i, 2);
      mbar_init(bars + BAR_WOLO, 1); mbar_init(bars + BAR_WOHI, 1);
#pragma unroll
      for (int i = 0; i < 8; i++) mbar_init(bars + BAR_SLAB + 8 * i, 1);
#pragma unroll
      for (int i = 0; i < 5; i++) mbar_init(bars + BAR_KREQ + 8 * i, 4);
      asm volatile("fence.mbarrier_init.release.cluster;" ::: "memory");
    }
    bar_sync(6, 128);
    bar_arrive(5, 384); bar_arrive(10, 256);
    asm volatile("setmaxnreg.dec.sync.aligned.u32 40;");
    const int uw = __shfl_sync(~0u, (tid >> 5) & 3, 0), t = tid - 384;
    uint32_t ep;
    LOAD_EP(cta + (tid >> 10));
    if (uw == 0) {
      if (lane == 0) {
        mbar_wait(bars + BAR_FULL, 0);
        prefetch_l2((const char*)prm.wqkv + 192 * 3072 + cta * 7680, 7680);
        prefetch_l2((const char*)prm.x + (rb * 8 + hg) * 16384, 16384);
#pragma unroll 1
        for (int s = 0; s < 5; s++) {
          const int sl = s < 3 ? s : s - 3;
          mbar_wait(bars + BAR_FULL + 8 * sl, s >= 3);
          mbar_expect_tx(bars + BAR_FULL + 8 * sl, STAGE);
          mbar_wait(bars + BAR_FREE + 8 * s, 0);
          tma3d(sb + sl * STAGE + 16384, &mw, hg * 64, (s + 3) * 64, 0, bars + BAR_FULL + 8 * sl);
          tma2d(sb + sl * STAGE, &mx, (s + 3) * 64, rb * 128, bars + BAR_FULL + 8 * sl);
        }
        prefetch_l2((const char*)prm.wo + cta * 4096, 4096);
      }
    } else if (uw < 3) {
      sts128(sb + SM_B + ((uw - 1) * 2 + (lane >> 4)) * U_CH + (lane & 15) * 16, 0, 0, 0, 0);
      const int mine = (lane & 7) - (cta & 1) * 4;
      const uint32_t dst = (unsigned)mine < 4u ? sb + SM_B + mine * U_CH + 256 + (lane >> 3) * 16 : sb + SM_B + 17536 + ((lane & 3) + 4 + (lane >> 3)) * 16;
      const uint32_t dstep = (unsigned)mine < 4u ? 128 : 0;
#pragma unroll 1
      for (int b = uw - 1 - NFL; b < 16; b += 2) {
        const uint32_t buf = sb + SM_LAND + (b & 7) * 2048, bar = bars + BAR_SLAB + 8 * (b & 7);
        if (b >= 0) {
          uint32_t r[16];
          mbar_wait(bar, b >> 3);
#pragma unroll
          for (int i = 0; i < 4; i++) ldsm4t(buf + i * 512 + lane * 16, r[4 * i], r[4 * i + 1], r[4 * i + 2], r[4 * i + 3]);
#pragma unroll
          for (int i = 0; i < 4; i++) stsm4(dst + (b * 2 + (i >> 1)) * dstep + (i & 1) * 64, r[4 * i], r[4 * i + 1], r[4 * i + 2], r[4 * i + 3]);
        }
        if (b + NFL < 16 && lane == 0) {
          const uint32_t nb = (b + NFL) & 7;
          mbar_expect_tx(bars + BAR_SLAB + 8 * nb, 2048); tma2d(sb + SM_LAND + nb * 2048, &mu, (cta >> 1) * 8, (b + NFL) * 128, bars + BAR_SLAB + 8 * nb);
        }
        __syncwarp();
      }
      bar_arrive(9, 224);
    } else {
      st_pkt(g_kvf + hg * 512 + rb * 32 + lane, ep, ep, ep, ep);
#pragma unroll 1
      for (int i = 0; i < 32; i += 2) {
        st_pkt(g_y + cta * 1024 + i * 32 + lane, ep, ep, ep, ep); st_pkt(g_y + cta * 1024 + i * 32 + 32 + lane, ep, ep, ep, ep);
        __nanosleep(100);
      }
      bar_arrive(9, 224);
      bar_sync(13, 288);
      if (lane == 0) {
        mbar_expect_tx(bars + BAR_WOLO, 65536); mbar_expect_tx(bars + BAR_WOHI, 65536);
#pragma unroll 1
        for (int p = 0; p < 4; p++) tma2d(sb + p * 16384, &mo, (cta & 3) * 128 + (((p >> 1) ^ p) & 1) * 64, (p >> 1) * 256, bars + BAR_WOLO);
      }
    }
    __syncwarp();
    bar_sync(4, 384);
    {
      const uint4* src = g_kvp + ((hg * 16 + rb) * 16 + (lane >> 3) * 4) * 32 + uw * 8 + (lane & 7);
      float s0, s1, s2, s3, sz; int it = 0; bool ok;
#pragma unroll 1
      do {
        uint4 pk[4];
#pragma unroll
        for (int i = 0; i < 4; i++) pk[i] = ld_pkt(src + i * 32);
        ok = __all_sync(~0u, ((mism(pk[0].x, pk[1].x, tag) | mism(pk[2].x, pk[3].x, tag)) & 0xFF) == 0);
        s0 = s1 = s2 = s3 = sz = 0.f;
#pragma unroll
        for (int i = 0; i < 4; i++) {
          s0 += __uint_as_float(pk[i].x & ~0xFFu); s1 += __uint_as_float(pk[i].y); s2 += __uint_as_float(pk[i].z); s3 += __uint_as_float(pk[i].w);
          sz += __uint_as_float(__byte_perm(__byte_perm(pk[i].y, pk[i].z, 0x0400), pk[i].w, 0x4210));
        }
#pragma unroll
        for (int o = 8; o <= 16; o <<= 1) {
          s0 += __shfl_xor_sync(~0u, s0, o); s1 += __shfl_xor_sync(~0u, s1, o); s2 += __shfl_xor_sync(~0u, s2, o); s3 += __shfl_xor_sync(~0u, s3, o); sz += __shfl_xor_sync(~0u, sz, o);
        }
        if (ok && lane < 8) st_pkt(g_kvf + hg * 512 + rb * 32 + uw * 8 + lane, pack_bf16(s0, s1), pack_bf16(s2, s3), pack_bf16(sz, sz), tag);
      } while (!ok && ++it < (1 << 16));
    }
    {
      const uint4* src = g_kvf + hg * 512 + t;
      bool bad; int it = 0;
#pragma unroll 1
      do {
        uint4 pk[4];
#pragma unroll
        for (int i = 0; i < 4; i++) pk[i] = ld_pkt(src + i * 128);
        bad = __any_sync(~0u, mism(pk[0].w, pk[1].w, tag) | mism(pk[2].w, pk[3].w, tag));
#pragma unroll
        for (int i = 0; i < 4; i++) {
          const uint32_t dst = sb + SM_V + (uw + 4 * i) * 384 + lane * 4;
          if (!bad) { sts32(dst, pk[i].x); sts32(dst + 128, pk[i].y); sts32(dst + 256, pk[i].z); }
        }
      } while (bad && ++it < (1 << 16));
      fence_async();
    }
    bar_arrive(7, 384);
    bar_sync(14, 384);
    if (lane == 0) tma2d(sb + (4 + uw) * 16384, &mo, (cta & 3) * 128 + (((uw >> 1) ^ uw) & 1) * 64, (uw >> 1) * 256 + 128, bars + BAR_WOHI);
    __syncwarp();
    bar_sync(15, 256);
    asm volatile("setmaxnreg.inc.sync.aligned.u32 56;");
    {
      uint32_t f; int it = 0;
      if (uw < 2) bar_sync(12, 192); else bar_sync(11, 192);
      __nanosleep(YDELAY);
      const int jp = (cta & 3) + (uw >> 1) * 4, pos = (uw & 1) * 16 + (lane >> 1);
      const uint4* src = g_y + (((cta >> 2) * 16 + (lane & 1) * 8) * 8 + jp) * 32 + pos;
      __nv_bfloat16* op = prm.out + 512 + (cta >> 2) * 16 + (lane & 1) * 8 + (size_t)(256 * jp + 32 * (pos & 3) + 2 * (pos >> 2)) * 1024;
      uint4 v[8];
      it = 0;
#pragma unroll 1
      do {
#pragma unroll
        for (int i = 0; i < 8; i++) v[i] = ld_pkt(src + i * 256);
        f = mism(v[0].x, v[1].x, tag) | mism(v[2].x, v[3].x, tag) | mism(v[4].x, v[5].x, tag) | mism(v[6].x, v[7].x, tag);
      } while (__any_sync(~0u, f & 1) && ++it < (1 << 16));
#define ROW(O, F, S, M) stg128(op + (O) * 1024, __byte_perm(v[0].F, v[1].F, S) & M, __byte_perm(v[2].F, v[3].F, S) & M, __byte_perm(v[4].F, v[5].F, S) & M, __byte_perm(v[6].F, v[7].F, S) & M)
      ROW(0, x, 0x5410, 0xFFFEFFFEu); ROW(1, x, 0x7632, ~0u); ROW(16, y, 0x5410, ~0u); ROW(17, y, 0x7632, ~0u);
      ROW(128, z, 0x5410, ~0u); ROW(129, z, 0x7632, ~0u); ROW(144, w, 0x5410, ~0u); ROW(145, w, 0x7632, ~0u);
    }

    return;
  }
  const int warp = __shfl_sync(~0u, tid >> 5, 0);
  const int g = lane >> 2, c = lane & 3;
  if (warp < 8) {
    la = ldg64(prm.w_phi + hg * 1024 + tid * 4); asm volatile("ld.global.u32 %0, [%1];" : "=r"(ldt) : "l"(g_epoch + cta + (tid >> 10)));
    bar_sync(5, 384);
    asm volatile("setmaxnreg.inc.sync.aligned.u32 160;");
    const int w = warp >> 2, wi = warp & 3;
    const uint32_t ep = ldt;
    uint4* const kvp_dst = g_kvp + ((hg * 16 + warp * 2) * 16 + rb) * 32 + lane;
    uint4* const o_dst = g_o + ((rb * 8 + warp) * 32 + hg * 4) * 32 + lane;
    float acc[96];
    mbar_wait(bars + BAR_FULL, 0);
    {
      const bool el = (tid & 127) == 0;
      uint32_t kb = bars + BAR_KREQ;
#pragma unroll
      for (int f = 0; f < 8; f++) {
        const uint32_t aa = sb + (f % 3) * STAGE;
        wg_fence();
#pragma unroll
        for (int k = 0; k < 4; k++) wg_ss192(acc, DSW(aa + w * 8192 + k * 32, 16), DSW(aa + 16384 + k * 2048, 8192), (f | k) != 0);
        wg_commit();
        if (f == 7) break;
        wg_wait<1>();
        if (f > 0) {
          if (el) mbar_arrive(bars + BAR_FREE + 8 * (f - 1));
          st_pkt(f < 3 ? kvp_dst + (f - 1) * 512 : o_dst + (f - 3) * 32, ep, ep, ep, ep);
        }
        if (f >= 2 && f <= 5) slice(kb);
        mbar_wait(bars + BAR_FULL + 8 * ((f + 1) % 3), ((f + 1) / 3) & 1);
      }
    }
    {
      const int h = warp >> 1, k = tid >> 2;
      mbar_wait(bars + BAR_FREE + 40, 0);
#pragma unroll
      for (int e = 0; e < 2; e++) {
        const uint32_t v = e ? la.y : la.x;
        sts128(sb + SM_WPHI + k * 128 + (((2 * c + e) ^ (k & 7)) << 4), h == 0 ? v : 0u, h == 1 ? v : 0u, h == 2 ? v : 0u, h == 3 ? v : 0u);
      }
      sts32(sb + SM_ONES + tid * 4, 0x3F803F80u);
      fence_async();
      bar_sync(1, 256);
    }
    wg_wait<0>();
    pin<96>(acc);
    const int r16 = (lane & 7) + ((lane >> 3) & 1) * 8, sx = lane & 7, sch = lane >> 4;
    const uint32_t pka = sb + SM_PK + (c >> 1) * 16384 + (warp * 16 + g) * 128 + ((((c & 1) * 4 + (c & 2)) ^ g) << 4);
    uint32_t pr[16], qf[16];
    {
      float pp[32];
#pragma unroll
      for (int i = 0; i < 16; i++) { pr[i] = pack_bf16(acc[32 + 2 * i], acc[33 + 2 * i]); asm volatile("" : "+r"(pr[i])); }
      wg_fence();
#pragma unroll
      for (int h = 0; h < 4; h++) wg_rs64(pp, pr[4 * h], pr[4 * h + 1], pr[4 * h + 2], pr[4 * h + 3], DSW(sb + SM_WPHI + h * 2048, 8192), h != 0);
      wg_commit();
      bar_arrive(13, 288);
#pragma unroll
      for (int h = 0; h < 4; h++)
        stsm4(sb + SM_V + (h >> 1) * 8192 + (warp * 16 + r16) * 64 + ((((h & 1) * 2 + sch) ^ (sx >> 1)) << 4), pack_bf16(acc[64 + 8 * h], acc[65 + 8 * h]), pack_bf16(acc[66 + 8 * h], acc[67 + 8 * h]),
              pack_bf16(acc[68 + 8 * h], acc[69 + 8 * h]), pack_bf16(acc[70 + 8 * h], acc[71 + 8 * h]));
#pragma unroll
      for (int i = 0; i < 16; i++) { qf[i] = pack_bf16(acc[2 * i], acc[2 * i + 1]); asm volatile("" : "+r"(qf[i])); }
      wg_wait<0>();
      pin<32>(pp);
#pragma unroll
      for (int i = 0; i < 8; i++) { pr[i] = pack_bf16(pp[4 * i], pp[4 * i + 1]); pr[8 + i] = pack_bf16(pp[4 * i + 2], pp[4 * i + 3]); }
    }
#pragma unroll 1
    for (int pass = 0; pass < 2; pass++) {
      uint32_t o[32];
      dual_softmax2(pr, o);
      if (pass) bar_sync(1, 256); else bar_sync(2, 256);
#pragma unroll
      for (int i = 0; i < 8; i++) sts128((pka ^ ((i & 3) * 16)) + (i >> 2) * 1024, o[4 * i], o[4 * i + 1], o[4 * i + 2], o[4 * i + 3]);
      fence_async();
      if (pass) break;
      bar_sync(1, 256);
      float kv[40], pq[32];
      wg_fence();
#pragma unroll
      for (int k = 0; k < 8; k++) wg_tt40(kv + 20 * (k & 1), DSW(sb + SM_PK + w * 16384 + k * 2048, 8192), make_desc(sb + SM_V + w * 8192 + k * 1024, SM_ONES - SM_V - w * 8192 - k * 1024, 512, 2), k > 1);
      wg_commit();
#pragma unroll
      for (int h = 0; h < 4; h++) wg_rs64(pq, qf[4 * h], qf[4 * h + 1], qf[4 * h + 2], qf[4 * h + 3], DSW(sb + SM_WPHI + h * 2048, 8192), h != 0);
      wg_commit();
      wg_wait<1>();
      pin<40>(kv);
      const bool hi = wi >> 1;
#define KV(i) __float_as_uint(hi ? kv[8 + (i)] + kv[28 + (i)] : kv[i] + kv[20 + (i)])
#pragma unroll
      for (int half = 0; half < 2; half++) {
        const uint32_t zz = __float_as_uint(kv[16 + 2 * half] + kv[36 + 2 * half]);
        st_pkt(kvp_dst + half * 512, __byte_perm(KV(2 * half), tag, 0x3214), __byte_perm(KV(1 + 2 * half), zz, 0x3215), __byte_perm(KV(4 + 2 * half), zz, 0x3216), __byte_perm(KV(5 + 2 * half), zz, 0x3217));
      }
      bar_arrive(4, 384);
      wg_wait<0>();
      pin<32>(pq);
#pragma unroll
      for (int i = 0; i < 8; i++) { pr[i] = pack_bf16(pq[4 * i], pq[4 * i + 1]); pr[8 + i] = pack_bf16(pq[4 * i + 2], pq[4 * i + 3]); }
    }
    bar_sync(7, 384);
    {
      float nd[48];
      wg_fence();
#pragma unroll
      for (int h = 0; h < 4; h++) wg_ss24(nd + 12 * h, DSW(sb + SM_PK + w * 8192 + (h >> 1) * 16384 + (h & 1) * 64, 16), make_desc(sb + SM_V + h * 1536, 384, 128, 0), 0);
#pragma unroll
      for (int h = 0; h < 4; h++) wg_ss24(nd + 12 * h, DSW(sb + SM_PK + w * 8192 + (h >> 1) * 16384 + (h & 1) * 64 + 32, 16), make_desc(sb + SM_V + h * 1536 + 768, 384, 128, 0), 1);
      wg_commit();
      wg_wait<0>();
      pin<48>(nd);
      bar_arrive(14, 384);
#pragma unroll
      for (int h = 0; h < 4; h++) {
        const float* n = nd + 12 * h;
        float i0 = rcp(n[8] + 1e-6f), i1 = rcp(n[10] + 1e-6f);
        uint32_t o0 = pack_bf16(n[0] * i0, n[1] * i0), o1 = pack_bf16(n[2] * i1, n[3] * i1), o2 = pack_bf16(n[4] * i0, n[5] * i0), o3 = pack_bf16(n[6] * i1, n[7] * i1);
        st_pkt(o_dst + h * 32, (o0 & ~1u) | (tag & 1), o1, o2, o3);
      }
    }
    const int rt = rb * 2 + (gi & 1), ct = cta & 3;
    {
      float o2[64];
      uint4 af[16];
      const uint4* src = g_o + ((rt * 4 + wi) * 32 + w * 16) * 32 + lane;
      mbar_wait(bars + BAR_WOLO, 0);
      __nanosleep(ODELAY);
#pragma unroll
      for (int i = 0; i < 16; i++) { af[i] = ld_pkt(src + i * 32); if (i < 15) __nanosleep(GPACE); }
#define BADG(G) ((mism(af[4 * (G)].x, af[4 * (G) + 1].x, tag) | mism(af[4 * (G) + 2].x, af[4 * (G) + 3].x, tag)) & 1)
#pragma unroll
      for (int grp = 0; grp < 4; grp++) {
        uint4* a = af + 4 * grp;
#pragma unroll 1
        for (int it = 0; __any_sync(~0u, BADG(grp)) && it < (1 << 16); it++) {
#pragma unroll
          for (int i = 0; i < 4; i++) a[i] = ld_pkt(src + (4 * grp + i) * 32);
        }
#pragma unroll
        for (int i = 0; i < 4; i++) asm volatile("and.b32 %0, %0, -2;" : "+r"(a[i].x));
      }
      uint32_t xs = sb + 16384 + (tid & 127) * 16 + w * 32768, tw = sb + 65536 + w * 32768 + 16384 + wi * 2048 + r16 * 128 + ((sch ^ sx) << 4);
      uint32_t tr = sb + 65536 + w * 32768 + 16384 + wi * 2048 + (lane >> 3) * 128 + ((sx ^ (lane >> 3)) << 4);
      __nv_bfloat16* op = prm.out + (size_t)(rt * 64 + wi * 16 + (lane >> 3)) * 1024 + ct * 128 + w * 64 + sx * 8;
      asm volatile("" : "+r"(xs), "+r"(tw), "+r"(tr), "+l"(op));
      mbar_wait(bars + BAR_WOHI, 0);
      bar_sync(8, 384);
      wg_fence();
#pragma unroll
      for (int i = 0; i < 16; i++) wg_rs64(o2 + 32, af[i].x, af[i].y, af[i].z, af[i].w, DSW(sb + (i >> 3) * 65536 + w * 32768 + 16384 + (i & 7) * 2048, 16384), i != 0);
      wg_commit();
#pragma unroll
      for (int i = 0; i < KSPLIT; i++) wg_rs64(o2, af[i].x, af[i].y, af[i].z, af[i].w, DSW(sb + (i >> 3) * 65536 + w * 32768 + (i & 7) * 2048, 16384), i != 0);
      wg_commit();
      wg_wait<1>();
      pin<32>(o2 + 32);
#pragma unroll
      for (int i = 0; i < 8; i++)
        sts128(xs + i * 2048, __float_as_uint(o2[32 + 4 * i]), __float_as_uint(o2[33 + 4 * i]), __float_as_uint(o2[34 + 4 * i]), __float_as_uint(o2[35 + 4 * i]));
      wg_fence();
#pragma unroll
      for (int i = KSPLIT; i < 16; i++) wg_rs64(o2, af[i].x, af[i].y, af[i].z, af[i].w, DSW(sb + (i >> 3) * 65536 + w * 32768 + (i & 7) * 2048, 16384), 1);
      wg_commit();
      bar_sync(1, 256);
      uint32_t px[32];
#pragma unroll
      for (int i = 0; i < 8; i++) lds128((xs ^ 32768) + i * 2048, px[4 * i], px[4 * i + 1], px[4 * i + 2], px[4 * i + 3]);
      wg_wait<0>();
      pin<32>(o2);
#pragma unroll
      for (int i = 0; i < 4; i++) {
#define OB(j) pack_bf16(o2[8 * i + 2 * (j)] + __uint_as_float(px[8 * i + 2 * (j)]), o2[8 * i + 2 * (j) + 1] + __uint_as_float(px[8 * i + 2 * (j) + 1]))
        stsm4(tw ^ (i * 32), OB(0), OB(1), OB(2), OB(3));
      }
      __syncwarp();
#pragma unroll
      for (int i = 0; i < 4; i++) lds128((tr ^ ((i & 1) * 64)) + i * 512, px[4 * i], px[4 * i + 1], px[4 * i + 2], px[4 * i + 3]);
#pragma unroll
      for (int i = 0; i < 4; i++) stg128(op + i * 4096, px[4 * i], px[4 * i + 1], px[4 * i + 2], px[4 * i + 3]);
    }
    if (tid == 0) g_epoch[cta] = tag;

  } else {
    const int ch = warp & 3;
    const uint32_t cb = sb + SM_B + ch * U_CH, stg = sb + SM_ST + ch * ST_SZ;
    const float dt = bf_lo(pack_bf16(expf(bf_lo(ldt)), 0.f));
    sts32(bars + 320 + ch * 4, dskb);
    const uint32_t aoff = ((lane & 7) + ((lane >> 3) & 1) * 8) * 128 + (((lane >> 4) ^ (lane & 7)) << 4);
    const uint32_t boff = (32 + (lane & 7)) * 128 + (((lane >> 3) ^ (lane & 7)) << 4);
    uint32_t ce = bmax2(bmax2(cr.x & 0x7FFF7FFFu, cr.y & 0x7FFF7FFFu), bmax2(ci.x & 0x7FFF7FFFu, ci.y & 0x7FFF7FFFu));
    ce = min(max(__reduce_max_sync(~0u, max(ce & 0xFFFFu, ce >> 16)) >> 7, 8u), 250u);
    const float csc = __uint_as_float((261u - ce) << 23);
    float kacc[6][4];
#pragma unroll
    for (int i = 0; i < 6; i++) { kacc[i][0] = kacc[i][1] = kacc[i][2] = kacc[i][3] = 0.f; }
    const uint32_t stg2 = sb + SM_Z + ch * Z_CH;
#pragma unroll 1
    for (int rd = 0; rd < 2; rd++) {
      Cx w1[2], w2[2], w8[2], w64[2], w128[2], w256[2], e0[2];
#pragma unroll
      for (int e = 0; e < 2; e++) {
#define SELH(v) (e ? bf_hi(v) : bf_lo(v))
        const float ar = -bf_lo(pack_bf16(ex2(SELH(la.x) * LOG2E), 0.f)) * dt, th = SELH(ai.x) * dt;
        const float l2 = ar * LOG2E;
        const float rh = th * 0.15915494309189535f, rl = fmaf(th, 0.15915494309189535f, -rh) + th * 6.4206382e-09f;
        e0[e] = {csc * SELH(cr.x), -csc * SELH(ci.x)};
        w1[e] = cpow(l2, rh, rl, 1.f); w64[e] = cpow(l2, rh, rl, 64.f);
        w2[e] = csqr(w1[e]); w8[e] = csqr(csqr(w2[e])); w128[e] = csqr(w64[e]); w256[e] = csqr(w128[e]);
      }
      la.x = la.y; ai.x = ai.y; cr.x = cr.y; ci.x = ci.y;
      const uint32_t st = (lane < 16 ? stg : stg2) + (lane & 15) * 8;
#define PUT(row, z) sts64((st ^ (((row) & 7) << 4)) + (row) * 128, z[0], z[1])
#define PH(z) pack_h((z).r, (z).i)
#define BOTH _Pragma("unroll") for (int e = 0; e < 2; e++)
      {
        uint32_t T[8][2]; Cx W[3][2];
        BOTH {
          const Cx t2 = csqr(w8[e]), t4 = csqr(t2), t6 = cmul(t4, t2);
          const uint32_t p8 = pack_h(-w8[e].i, w8[e].r);
          T[0][e] = 0x00003C00u; T[1][e] = PH(w8[e]); T[2][e] = PH(t2); T[4][e] = PH(t4); T[6][e] = PH(t6);
          T[3][e] = hcmul(T[2][e], T[1][e], p8); T[5][e] = hcmul(T[4][e], T[1][e], p8); T[7][e] = hcmul(T[6][e], T[1][e], p8);
          W[0][e] = w64[e]; W[1][e] = w128[e]; W[2][e] = cmul(W[1][e], w64[e]);
        }
#pragma unroll
        for (int i = 0; i < 8; i++) PUT(i, T[i]);
#pragma unroll
        for (int m = 0; m < 3; m++) {
          uint32_t b[2], bp[2], x[2];
          BOTH { b[e] = PH(W[m][e]); bp[e] = pack_h(-W[m][e].i, W[m][e].r); }
          PUT(8 * m + 8, b);
#pragma unroll
          for (int i = 1; i < 8; i++) { BOTH x[e] = hcmul(T[i][e], b[e], bp[e]); PUT(8 * m + 8 + i, x); }
        }
      }
      if (rd == 0) bar_sync(10, 256);
      {
        Cx w512[2], gq[2], hq[2]; uint32_t c1[2], c1p[2], c256[2], c256p[2];
        BOTH {
          w512[e] = csqr(w256[e]); gq[e] = e0[e]; hq[e] = e0[e];
          c1[e] = pack_h(w1[e].r, -w1[e].i); c1p[e] = pack_h(w1[e].i, w1[e].r); c256[e] = pack_h(w256[e].r, -w256[e].i); c256p[e] = pack_h(w256[e].i, w256[e].r);
        }
#pragma unroll
        for (int j = 0; j < 4; j++) {
          uint32_t G[2], x[2], H[2];
          BOTH { G[e] = PH(gq[e]); x[e] = hcmul(G[e], c1[e], c1p[e]); }
          PUT(32 + 2 * j, G); PUT(33 + 2 * j, x);
          BOTH x[e] = hcmul(G[e], c256[e], c256p[e]);
          PUT(40 + j, x);
          if (j == 3 && lane == 0) mbar_arrive(bars + BAR_KREQ + 8 * rd);
          if (j == 2) { BOTH x[e] = hcmul(x[e], c256[e], c256p[e]); PUT(45, x); BOTH x[e] = hcmul(x[e], c256[e], c256p[e]); PUT(47, x); }
          BOTH { if (j < 3) gq[e] = cmulc(gq[e], w2[e]); hq[e] = cmulc(hq[e], w512[e]); H[e] = PH(hq[e]); }
          PUT(j == 0 ? 44 : 46 + 2 * j, H);
          if (j < 3) { BOTH x[e] = hcmul(H[e], c256[e], c256p[e]); PUT(j == 0 ? 46 : 47 + 2 * j, x); }
        }
      }
      __syncwarp();
#pragma unroll 1
      for (int k = 0; k < 2; k++) {
        uint32_t fa[8][4], fb[6][4];
        const uint32_t buf = k ? stg2 : stg;
#pragma unroll
        for (int i = 0; i < 6; i++) ldsm4(buf + (boff ^ ((i / 3) * 64)) + (i % 3) * 1024, fb[i][0], fb[i][1], fb[i][2], fb[i][3]);
#pragma unroll
        for (int i = 0; i < 8; i++) ldsm4(buf + (aoff ^ ((i >> 1) * 32)) + (i & 1) * 2048, fa[i][0], fa[i][1], fa[i][2], fa[i][3]);
#pragma unroll
        for (int ks = 0; ks < 4; ks++)
#pragma unroll
          for (int mt = 0; mt < 2; mt++)
#pragma unroll
            for (int nt = 0; nt < 3; nt++) mma16816h(kacc[mt * 3 + nt], fa[2 * ks + mt], fb[(ks >> 1) * 3 + nt][2 * (ks & 1)], fb[(ks >> 1) * 3 + nt][2 * (ks & 1) + 1]);
      }
      __syncwarp();
      if (lane == 0) { sts32(bars + 336 + ch * 4, __float_as_uint(kacc[3][0] + kacc[4][0] + kacc[5][0])); mbar_arrive(bars + BAR_KDONE + 8 * rd); }
    }
    {
      const float fin = 2.f * dt * __uint_as_float((ce - 7u) << 23);
#pragma unroll
      for (int i = 0; i < 6; i++) { kacc[i][0] *= fin; kacc[i][1] *= fin; kacc[i][2] *= fin; kacc[i][3] *= fin; }
    }
    asm volatile("setmaxnreg.inc.sync.aligned.u32 152;");
    const float dsk = bf_lo(lds32(bars + 320 + ch * 4));
    uint32_t ep; LOAD_EP(128 + cta * 4 + ch + (tid >> 10));
    bar_sync(9, 224);
    {
#define ONES(mask, e) ((((mask) >> (e)) & 1u) * 0x3F80u + (((mask) >> ((e) + 1)) & 1u) * 0x3F800000u)
      const uint32_t la_ = cb + 256 - 16 + ((lane & 15) + (lane >> 4)) * 16;
      const uint32_t k2 = ((g & 1) ? 0x3Eu : 0x1C0u) << (g & 6) >> (2 * c), k3 = ((g & 1) ? 0x3FE0u : 0x1FC000u) << (g & 6) >> (2 * c);
      uint32_t pb[2][6];
#pragma unroll
      for (int t = 0; t < 2; t++) {
        pb[t][0] = ONES(k2, 1 - t); pb[t][1] = ONES(k2, 9 - t);
        pb[t][2] = ONES(k3, 1 - t); pb[t][3] = ONES(k3, 9 - t); pb[t][4] = ONES(k3, 17 - t); pb[t][5] = ONES(k3, 25 - t);
      }
      if (lane < 10) sts32(stg2 + lane * 4, 0u);
      uint32_t a1[2][2][4], a0[2][2][4], x[5][4];
#define ZLD(B) do { _Pragma("unroll") for (int i = 0; i < 2; i++) { ldsm4(la_ + (2 * (B) + i) * 256, a1[(B) & 1][i][0], a1[(B) & 1][i][1], a1[(B) & 1][i][2], a1[(B) & 1][i][3]); \
        if ((B) < 4) ldsm4(la_ - 32 + (2 * (B) + i) * 256, a0[(B) & 1][i][0], a0[(B) & 1][i][1], a0[(B) & 1][i][2], a0[(B) & 1][i][3]); } } while (0)
      ZLD(0);
#pragma unroll
      for (int B = 0; B < 6; B++) {
        float z[2][2][4], y[2][2][4];
        if (B < 4) {
#pragma unroll
          for (int i = 0; i < 4; i++) { float* q = y[i >> 1][i & 1]; const uint32_t* xx = a0[B & 1][i >> 1]; q[0] = q[1] = q[2] = q[3] = 0.f; mma16816(q, xx[0], xx[1], xx[2], xx[3], pb[i & 1][2], pb[i & 1][3]); }
        }
#pragma unroll
        for (int i = 0; i < 4; i++) { float* q = z[i >> 1][i & 1]; const uint32_t* xx = a1[B & 1][i >> 1]; q[0] = q[1] = q[2] = q[3] = 0.f; mma16816(q, xx[0], xx[1], xx[2], xx[3], pb[i & 1][0], pb[i & 1][1]); }
        if (B < 4) {
#pragma unroll
          for (int i = 0; i < 4; i++) { const uint32_t* xx = a1[B & 1][i >> 1]; mma16816(y[i >> 1][i & 1], xx[0], xx[1], xx[2], xx[3], pb[i & 1][4], pb[i & 1][5]); }
        }
        if (B < 5) ZLD(B + 1);
        if (B == 0) {
    {
      const uint32_t V = stg + T_V + 32;
      sts32(lane < 8 ? V - 32 + lane * 4 : V + (249 + lane) * 4, 0u);
      if (lane < 15) sts32(V + (281 + lane) * 4, 0u);
      __syncwarp();
      if (lane == 0) kacc[0][0] += dsk;
      const uint32_t h0 = c < 2 ? V + (127 + 2 * c) * 4 : stg + T_HH + (64 * (c - 2) - 1) * 2, h1 = c < 2 ? h0 + 10 : h0 + 2, hs = c < 2 ? 16 : 4;
#pragma unroll
      for (int mt = 0; mt < 2; mt++)
#pragma unroll
        for (int hf = 0; hf < 2; hf++) {
          const int i = 16 * mt + 8 * hf + g;
          sts32(V + (4 * i + c) * 4, pack_bf16(kacc[mt * 3][2 * hf + 1], kacc[mt * 3][2 * hf]));
          uint32_t v = pack_bf16(kacc[mt * 3 + 1][2 * hf], kacc[mt * 3 + 1][2 * hf + 1]);
          if (mt + hf > 0 || lane > 0) sts16(h0 + hs * i, v);
          sts16(h1 + hs * i, v >> 16);
          if (c < 2) sts32(h0 + 4 + hs * i, __byte_perm(v, v, 0x1010));
          if (mt + hf == 0 && lane == 2) { sts16(V + 255 * 4, v); sts32(V + 256 * 4, __byte_perm(v, v, 0x1010)); sts16(V + 257 * 4 + 2, v); }
          v = pack_bf16(kacc[mt * 3 + 2][2 * hf], kacc[mt * 3 + 2][2 * hf + 1]);
          sts16(stg + T_HH + (127 + 64 * c + i) * 2, v); sts16(stg + T_HH + (159 + 64 * c + i) * 2, v >> 16);
          if (mt + hf == 0 && lane == 0) { sts16(V + 281 * 4, v); sts16(V + 282 * 4 + 2, v); }
        }
      __syncwarp();
    }
        }
        if (B == 1) {
#pragma unroll
          for (int i = 0; i < 5; i++) { const uint32_t a = stg + T_V + lane * 8 + i * 256; lds64(a, x[i][0], x[i][1]); lds64(a + 8, x[i][2], x[i][3]); }
        }
        if (B == 2) {
          __syncwarp();
#pragma unroll
          for (int i = 0; i < 5; i++) {
            const uint32_t a = stg + T_V + (lane ^ ((lane >> 2) & 1)) * 32 + i * 1024, m = __byte_perm(x[i][2], x[i][1], 0x5432);
            sts128(a, m, x[i][2], __byte_perm(x[i][1], x[i][0], 0x5432), x[i][1]);
            sts128(a + 16, __byte_perm(x[i][3], x[i][2], 0x5432), x[i][3], m, x[i][2]);
          }
        }
        const uint32_t zs = stg2 + lane * 8 + B * 1024, zt = stg2 + Z_Z3 + ((lane * 8) ^ ((lane & 16) * 2)) + B * 1024;
#pragma unroll
        for (int i = 0; i < 2; i++) {
          sts64(zs + 40 + i * 512, pack_bf16(z[i][0][0], z[i][0][1]), pack_bf16(z[i][1][0], z[i][1][1]));
          sts64(zs + 296 + i * 512, pack_bf16(z[i][0][2], z[i][0][3]), pack_bf16(z[i][1][2], z[i][1][3]));
          if (B < 4) {
            sts64(zt + i * 512, pack_bf16(y[i][0][0], y[i][0][1]), pack_bf16(y[i][1][0], y[i][1][1]));
            sts64(zt + 256 + i * 512, pack_bf16(y[i][0][2], y[i][0][3]), pack_bf16(y[i][1][2], y[i][1][3]));
          }
        }
      }
    }
    __syncwarp();
    float acc[16][4];
#pragma unroll
    for (int j = 0; j < 16; j++) { acc[j][0] = acc[j][1] = acc[j][2] = acc[j][3] = 0.f; }
    const uint32_t ub = cb + 256 + g * 32 + c * 16;
    uint32_t vb[2];
#pragma unroll
    for (int h = 0; h < 2; h++) { const int e = 14 + g - 4 * c - 2 * h; vb[h] = stg + T_V + (e ^ ((e >> 2) & 2)) * 16 - 128; }
#define MMA2(c_, a, b) do { mma16816(c_, a[0][0], a[0][1], a[0][2], a[0][3], b[0], b[1]); } while (0)
#define MMA3(c_, a, b) do { mma16816(c_, a[1][0], a[1][1], a[1][2], a[1][3], b[2], b[3]); } while (0)
    uint32_t bn[4][4];
#pragma unroll
    for (int i = 0; i < 4; i++) lds128(ub - 32 + i * 1024, bn[i][0], bn[i][1], bn[i][2], bn[i][3]);
#define LDH(a, h, delta) lds128(vb[h] + (delta) * 128, a[h][0], a[h][1], a[h][2], a[h][3])
    uint32_t a[4][2][4];
#pragma unroll
    for (int q = 0; q < 4; q++) LDH(a[q], 0, 8 * q + 1);
#pragma unroll 1
    for (int r = 1; r < 8; r += 2) {
#pragma unroll
      for (int q = 0; q < 4; q++) LDH(a[q], 1, 8 * q + r);
#pragma unroll
      for (int m = 0; m < 4; m++) {
        uint32_t b[4][4];
#pragma unroll
        for (int i = 0; i < 16; i++) b[i >> 2][i & 3] = bn[i >> 2][i & 3];
        const uint32_t nx = m < 3 ? ub + (m + 1) * 256 - r * 32 : ub - (r + 2) * 32;
#pragma unroll
        for (int q = 0; q < 4; q++)
#pragma unroll
          for (int i = 0; i < 4; i++) if (m + 4 * i + q < 16) MMA2(acc[m + 4 * i + q], a[q], b[i]);
        __syncwarp();
#pragma unroll
        for (int i = 0; i < 4; i++) lds128(nx + i * 1024, bn[i][0], bn[i][1], bn[i][2], bn[i][3]);
        if (m == 3) {
#pragma unroll
          for (int q = 0; q < 4; q++) LDH(a[q], 0, 8 * q + r + 2);
        }
#pragma unroll
        for (int q = 0; q < 4; q++)
#pragma unroll
          for (int i = 0; i < 4; i++) if (m + 4 * i + q < 16) MMA3(acc[m + 4 * i + q], a[q], b[i]);
      }
    }
    asm volatile("setmaxnreg.dec.sync.aligned.u32 136;");
    bar_arrive(15, 256);
    uint4* const y_dst = g_y + (cta * 4 + ch) * 256 + lane;
#define PUBY(j) st_pkt(y_dst + (j) * 16, (pack_bf16(acc[j][0], acc[j][2]) & ~1u) | (tag & 1), pack_bf16(acc[j][1], acc[j][3]), \
                       pack_bf16(acc[(j) + 1][0], acc[(j) + 1][2]), pack_bf16(acc[(j) + 1][1], acc[(j) + 1][3]))
    {
      uint32_t a1[2][4], b[8][4];
      LDH(a[3], 1, 33);
      lds128((vb[0] ^ 32) + 36 * 128, a1[0][0], a1[0][1], a1[0][2], a1[0][3]); lds128((vb[1] ^ 32) + 36 * 128, a1[1][0], a1[1][1], a1[1][2], a1[1][3]);
#pragma unroll
      for (int m = 0; m < 8; m++) lds128(ub + m * 256 - 32, b[m][0], b[m][1], b[m][2], b[m][3]);
#pragma unroll
      for (int m = 0; m < 8; m++) MMA2(acc[m + 4], a[3], b[m]);
#pragma unroll
      for (int m = 0; m < 8; m++) MMA2(acc[m + 8], a1, b[m]);
#pragma unroll
      for (int m = 0; m < 8; m++) MMA3(acc[m + 8], a1, b[m]);
#pragma unroll
      for (int m = 0; m < 4; m++) MMA3(acc[m + 4], a[3], b[m]);
      __syncwarp();
#pragma unroll
      for (int m = 0; m < 4; m++) lds128(ub + (m + 8) * 256 - 32, b[m][0], b[m][1], b[m][2], b[m][3]);
      uint32_t kb[8][2], za[2][4][4];
      const uint32_t hh = stg + T_HH + (2 * g - c) * 4, z2 = stg2 + (8 * c + 2 * g) * 4, z3 = stg2 + Z_Z3 + ((64 * c + 8 * g) ^ ((c & 2) * 16));
#define LDB2(pi) do { const int i0 = 65 - 8 * (pi) + 2 * g - c; \
        _Pragma("unroll") for (int t = 0; t < 5; t++) { kb[t][0] = lds32(hh + (65 - 8 * (pi) - 16 * t) * 4); kb[t][1] = lds32(hh + (61 - 8 * (pi) - 16 * t) * 4); } \
        if (i0 > 63) kb[0][0] = 0; if (i0 > 67) kb[0][1] = 0; if (i0 < 64) kb[4][0] = 0; if (i0 < 68) kb[4][1] = 0; } while (0)
#define LDZ(G) do { _Pragma("unroll") for (int i = 0; i < 4; i++) { \
        const uint32_t p = (G) < 6 ? z2 + ((G) / 3) * 256 + (((G) % 3) * 4 + i) * 512 : z3 + (((G) - 6) * 4 + i) * 512; \
        lds64(p, za[(G) & 1][i][0], za[(G) & 1][i][1]); lds64(p + ((G) < 6 ? 128 : 256), za[(G) & 1][i][2], za[(G) & 1][i][3]); } } while (0)
      LDB2(0); LDZ(0);
      PUBY(0); PUBY(2);
#pragma unroll
      for (int m = 4; m < 8; m++) MMA3(acc[m + 4], a[3], b[m]);
#pragma unroll
      for (int m = 0; m < 4; m++) MMA2(acc[m + 12], a[3], b[m]);
#pragma unroll
      for (int m = 0; m < 4; m++) MMA3(acc[m + 12], a[3], b[m]);
#pragma unroll
      for (int G = 0; G < 8; G++) {
        uint32_t k2[8][2];
#pragma unroll
        for (int t = 0; t < 8; t++) { k2[t][0] = kb[t][0]; k2[t][1] = kb[t][1]; }
        __syncwarp();
        if (G < 7) LDZ(G + 1);
        if (G == 2) LDB2(1);
        if (G == 5) { PUBY(4); PUBY(6); bar_arrive(12, 192); }
        if (G == 5) {
#pragma unroll
          for (int t = 0; t < 8; t++) { kb[t][0] = lds32(stg + T_HH + (64 + 8 * t + g - c) * 4); kb[t][1] = lds32(stg + T_HH + (60 + 8 * t + g - c) * 4); }
          if (g < c) kb[0][0] = 0; if (g < c + 4) kb[0][1] = 0;
        }
#pragma unroll
        for (int i = 0; i < 4; i++) {
          const uint32_t* z = za[G & 1][i];
          if (G < 6) {
            const int k = (G % 3) * 4 + i;
#pragma unroll
            for (int t = 4; t >= 0; t--) if (8 - t + k < 16) mma16816(acc[8 - t + k], z[0], z[1], z[2], z[3], k2[t][0], k2[t][1]);
          } else {
            const int k = (G - 6) * 4 + i;
#pragma unroll
            for (int t = 0; t < 8 - k; t++) mma16816(acc[8 + k + t], z[0], z[1], z[2], z[3], k2[t][0], k2[t][1]);
          }
        }
      }
    }
    if (lane == 0) sts32(bars + 336 + ch * 4, __float_as_uint(acc[8][0]) ^ __float_as_uint(acc[9][0]) ^ __float_as_uint(acc[10][0]) ^ __float_as_uint(acc[11][0]) ^ __float_as_uint(acc[12][0])
                         ^ __float_as_uint(acc[13][0]) ^ __float_as_uint(acc[14][0]) ^ __float_as_uint(acc[15][0]));
    bar_arrive(8, 384);
#pragma unroll
    for (int j = 8; j < 16; j += 2) PUBY(j);
    bar_arrive(11, 192);
    if (lane == 0) g_epoch[128 + cta * 4 + ch] = tag;

  }
}

typedef CUresult (*EncodeFn)(CUtensorMap*, CUtensorMapDataType, cuuint32_t, void*, const cuuint64_t*, const cuuint64_t*, const cuuint32_t*, const cuuint32_t*,
                             CUtensorMapInterleave, CUtensorMapSwizzle, CUtensorMapL2promotion, CUtensorMapFloatOOBfill);

extern "C" void kernel_launch(void* const* d_in, const int* in_sizes, int n_in, void* d_out, int out_size) {
  static const void* mapped[4] = {nullptr, nullptr, nullptr, nullptr};
  static CUtensorMap mx, mw, mo, mu;
  if (mapped[0] != d_in[0] || mapped[1] != d_in[1] || mapped[2] != d_in[3] || mapped[3] != d_in[4]) {
    void* fn = nullptr; cudaDriverEntryPointQueryResult qr;
    cudaGetDriverEntryPoint("cuTensorMapEncodeTiled", &fn, cudaEnableDefault, &qr);
    EncodeFn enc = (EncodeFn)fn;
    const cuuint32_t es[3] = {1, 1, 1};
    { cuuint64_t dims[2] = {512, 2048}, str[1] = {1024}; cuuint32_t box[2] = {64, 128};
      enc(&mx, CU_TENSOR_MAP_DATA_TYPE_BFLOAT16, 2, d_in[0], dims, str, box, es, CU_TENSOR_MAP_INTERLEAVE_NONE, CU_TENSOR_MAP_SWIZZLE_128B, CU_TENSOR_MAP_L2_PROMOTION_L2_128B, CU_TENSOR_MAP_FLOAT_OOB_FILL_NONE); }
    { cuuint64_t dims[3] = {512, 512, 3}, str[2] = {3072, 1024}; cuuint32_t box[3] = {64, 64, 3};
      enc(&mw, CU_TENSOR_MAP_DATA_TYPE_BFLOAT16, 3, d_in[1], dims, str, box, es, CU_TENSOR_MAP_INTERLEAVE_NONE, CU_TENSOR_MAP_SWIZZLE_128B, CU_TENSOR_MAP_L2_PROMOTION_L2_128B, CU_TENSOR_MAP_FLOAT_OOB_FILL_NONE); }
    { cuuint64_t dims[2] = {512, 512}, str[1] = {1024}; cuuint32_t box[2] = {64, 128};
      enc(&mo, CU_TENSOR_MAP_DATA_TYPE_BFLOAT16, 2, d_in[3], dims, str, box, es, CU_TENSOR_MAP_INTERLEAVE_NONE, CU_TENSOR_MAP_SWIZZLE_128B, CU_TENSOR_MAP_L2_PROMOTION_L2_128B, CU_TENSOR_MAP_FLOAT_OOB_FILL_NONE); }
    { cuuint64_t dims[2] = {512, 2048}, str[1] = {1024}; cuuint32_t box[2] = {8, 128};
      enc(&mu, CU_TENSOR_MAP_DATA_TYPE_BFLOAT16, 2, d_in[4], dims, str, box, es, CU_TENSOR_MAP_INTERLEAVE_NONE, CU_TENSOR_MAP_SWIZZLE_NONE, CU_TENSOR_MAP_L2_PROMOTION_L2_128B, CU_TENSOR_MAP_FLOAT_OOB_FILL_NONE); }
    cudaFuncSetAttribute(fused_kernel, cudaFuncAttributeMaxDynamicSharedMemorySize, SM_TOTAL);
    mapped[0] = d_in[0]; mapped[1] = d_in[1]; mapped[2] = d_in[3]; mapped[3] = d_in[4];
  }
  Params p;
  p.x = (const __nv_bfloat16*)d_in[0]; p.wqkv = (const __nv_bfloat16*)d_in[1]; p.wo = (const __nv_bfloat16*)d_in[3];
  p.w_phi = (const __nv_bfloat16*)d_in[2]; p.u = (const __nv_bfloat16*)d_in[4]; p.log_a = (const __nv_bfloat16*)d_in[5]; p.a_im = (const __nv_bfloat16*)d_in[6];
  p.c_re = (const __nv_bfloat16*)d_in[7]; p.c_im = (const __nv_bfloat16*)d_in[8]; p.log_dt = (const __nv_bfloat16*)d_in[9]; p.d_skip = (const __nv_bfloat16*)d_in[10];
  p.out = (__nv_bfloat16*)d_out;
  fused_kernel<<<128, 512, SM_TOTAL, cudaStreamPerThread>>>(p, mx, mw, mo, mu);
}
```
